```python
import torch

def _softmax(x, axis=-1):
    return torch.softmax(x, dim=axis)
def _gelu(x):
    return torch.nn.functional.gelu(x, approximate="tanh")
def _silu(x):
    return torch.nn.functional.silu(x)
def _sigmoid(x):
    return torch.sigmoid(x)
def _layernorm(x, axis=-1, eps=1e-5):
    m = x.mean(dim=axis, keepdim=True)
    v = x.var(dim=axis, keepdim=True, unbiased=False)
    return (x - m) / torch.sqrt(v + eps)
def _scatter_add(tgt, idx, src, axis=0):
    return tgt.clone().index_add_(axis, idx, src)
def _segment_sum(src, seg, n):
    out = torch.zeros((n,) + src.shape[1:], dtype=src.dtype)
    return out.index_add_(0, seg, src)
def _pad(x, pw):
    flat = tuple(v for pair in reversed(pw) for v in pair)
    return torch.nn.functional.pad(x, flat)

kernel_name = 'concat_heads__ssm_conv_s5__ssm_conv_h3__prompt'

def setup_inputs():

    _w = (lambda a: (lambda t: t.to(torch.bfloat16) if t.is_floating_point() else t)(torch.as_tensor(a)))
    def _A_setup():
        B, S, D = 1, 2048, 640
        P = D
        Lambda_re = -0.5 * (lambda _x: torch.exp(torch.as_tensor(_x)))((lambda *s: torch.randn(*s, dtype=torch.bfloat16) * 0.2)(P))
        Lambda_im = (lambda *s: torch.randn(*s, dtype=torch.bfloat16) * 0.4)(P) * 1.0
        B_re = (lambda *s: torch.randn(*s, dtype=torch.bfloat16) * 0.2)(P, D) * (D ** -0.5)
        B_im = (lambda *s: torch.randn(*s, dtype=torch.bfloat16) * 0.2)(P, D) * (D ** -0.5)
        C_re = (lambda *s: torch.randn(*s, dtype=torch.bfloat16) * 0.2)(D, P) * (P ** -0.5)
        C_im = (lambda *s: torch.randn(*s, dtype=torch.bfloat16) * 0.2)(D, P) * (P ** -0.5)
        log_dt = (lambda *s: torch.randn(*s, dtype=torch.bfloat16) * 0.2)(P) * 0.3 - 2.0
        Dskip = (lambda *s: torch.randn(*s, dtype=torch.bfloat16) * 0.05)(D)
        return {
            "x": _w((lambda *s: torch.randn(*s, dtype=torch.bfloat16) * 0.05)(B, S, D)),
            "Lambda_re": _w(Lambda_re),
            "Lambda_im": _w(Lambda_im),
            "B_re": _w(B_re),
            "B_im": _w(B_im),
            "C_re": _w(C_re),
            "C_im": _w(C_im),
            "log_dt": _w(log_dt),
            "Dskip": _w(Dskip),
        }
    _A_in = _A_setup()

    def _B_setup():
        B, S, D = 1, 2048, 640
        ks = 4
        return {
            "q": _w((lambda *s: torch.randn(*s, dtype=torch.bfloat16) * 0.05)(B, S, D)),
            "k": _w((lambda *s: torch.randn(*s, dtype=torch.bfloat16) * 0.4)(B, S, D)),
            "v": _w((lambda *s: torch.randn(*s, dtype=torch.bfloat16) * 0.2)(B, S, D)),
            "shift_k": _w((lambda *s: torch.randn(*s, dtype=torch.bfloat16) * 0.4)(D, ks) * 0.5),
            "ssm_k": _w((lambda *s: torch.randn(*s, dtype=torch.bfloat16) * 0.4)(D, S) * (1.0 / S ** 0.5)),
            "ssm_D": _w((lambda *s: torch.randn(*s, dtype=torch.bfloat16) * 0.2)(D)),
        }
    _B_in = _B_setup()

    return {
        "A_x": _A_in["x"],
        "A_Lambda_re": _A_in["Lambda_re"],
        "A_Lambda_im": _A_in["Lambda_im"],
        "A_B_re": _A_in["B_re"],
        "A_B_im": _A_in["B_im"],
        "A_C_re": _A_in["C_re"],
        "A_C_im": _A_in["C_im"],
        "A_log_dt": _A_in["log_dt"],
        "A_Dskip": _A_in["Dskip"],
        "B_q": _B_in["q"],
        "B_k": _B_in["k"],
        "B_v": _B_in["v"],
        "B_shift_k": _B_in["shift_k"],
        "B_ssm_k": _B_in["ssm_k"],
        "B_ssm_D": _B_in["ssm_D"],
    }

def reference(A_x, A_Lambda_re, A_Lambda_im, A_B_re, A_B_im, A_C_re, A_C_im, A_log_dt, A_Dskip, B_q, B_k, B_v, B_shift_k, B_ssm_k, B_ssm_D):
    def _A_ref(x, Lambda_re, Lambda_im, B_re, B_im, C_re, C_im, log_dt, Dskip):
        Bsz, L, H = x.shape
        Lam = Lambda_re + 1j * Lambda_im
        Bmat = B_re + 1j * B_im
        Cmat = C_re + 1j * C_im
        dt = torch.exp(log_dt)
        Lam_bar = torch.exp(dt * Lam)
        B_bar = ((Lam_bar - 1.0) / Lam)[:, None] * Bmat
        Bu = torch.einsum("bld,pd->blp", x + 0j, B_bar)
        h = torch.zeros_like(Bu[:, 0, :])
        hs = []
        for t in range(L):
            h = Lam_bar[None, :] * h + Bu[:, t, :]
            hs.append(h)
        hseq = torch.stack(hs, 1)
        y = 2.0 * torch.einsum("blp,dp->bld", hseq, Cmat).real + x * Dskip[None, None, :]
        return y

    def _B_ref(q, k, v, shift_k, ssm_k, ssm_D):
        B, S, D = q.shape
        ks = shift_k.shape[-1]
        k_pad = _pad(k, ((0, 0), (ks - 1, 0), (0, 0)))
        k_shift = torch.zeros_like(k)
        for t in range(ks):
            k_shift = k_shift + k_pad[:, t:t + S, :] * shift_k[:, ks - 1 - t][None, None, :]
        kv = k_shift * v
        L = 2 * S
        kv_pad = _pad(kv, ((0, 0), (0, S), (0, 0)))
        kf_pad = _pad(ssm_k, ((0, 0), (0, S)))
        kv_f = (lambda x, axes=(-2,-1): torch.fft.rfft2(x.float(), dim=axes))(kv_pad[:, None, :, :], axes=(1, 2))
        kf_f = (lambda x, axes=(-2,-1): torch.fft.rfft2(x.float(), dim=axes))(kf_pad[:, None, :], axes=(1, 2))
        kf_f = (lambda x, *d: x.permute(*d))(kf_f, 1, 2, 0)
        y_f = kv_f * kf_f[None, :, :, :]
        y = (lambda x, s, axes=(-2,-1): torch.fft.irfft2(x, s=s, dim=axes).to(torch.bfloat16))(y_f, (1, L), axes=(1, 2))[:, 0, :S, :]
        y = y + kv * ssm_D[None, None, :]
        return q * y

    a = _A_ref(A_x, A_Lambda_re, A_Lambda_im, A_B_re, A_B_im, A_C_re, A_C_im, A_log_dt, A_Dskip)
    b = _B_ref(B_q, B_k, B_v, B_shift_k, B_ssm_k, B_ssm_D)
    return torch.concatenate([a, b], axis=-1)
```

```cpp
#include <cuda_runtime.h>
#include <cuda_bf16.h>
#include <cuda.h>
#include <stdint.h>

#define ENABLE_A 1
#define ENABLE_B 1

constexpr int SEQ = 2048, DM = 640, OUTW = 1280;
constexpr int NA = 80, NB = 50;
constexpr int SMEM_BYTES = 232448;

template<int N, int TA, int TB, int SA, int SB> struct WSS;
template<int TA, int TB, int SA, int SB> struct WSS<128,TA,TB,SA,SB> {
  static __device__ __forceinline__ void run(float* d, uint32_t da, uint32_t db, int sc) {
    asm volatile("{\n.reg .pred p;\n.reg .b64 da, db;\nmov.b64 da, {%64, %71};\nmov.b64 db, {%65, %71};\nsetp.ne.b32 p, %66, 0;\nwgmma.mma_async.sync.aligned.m64n128k16.f32.bf16.bf16 {%0, %1, %2, %3, %4, %5, %6, %7, %8, %9, %10, %11, %12, %13, %14, %15, %16, %17, %18, %19, %20, %21, %22, %23, %24, %25, %26, %27, %28, %29, %30, %31, %32, %33, %34, %35, %36, %37, %38, %39, %40, %41, %42, %43, %44, %45, %46, %47, %48, %49, %50, %51, %52, %53, %54, %55, %56, %57, %58, %59, %60, %61, %62, %63}, da, db, p, %67, %68, %69, %70;\n}\n"
      : "+f"(d[0]), "+f"(d[1]), "+f"(d[2]), "+f"(d[3]), "+f"(d[4]), "+f"(d[5]), "+f"(d[6]), "+f"(d[7]), "+f"(d[8]), "+f"(d[9]), "+f"(d[10]), "+f"(d[11]), "+f"(d[12]), "+f"(d[13]), "+f"(d[14]), "+f"(d[15]), "+f"(d[16]), "+f"(d[17]), "+f"(d[18]), "+f"(d[19]), "+f"(d[20]), "+f"(d[21]), "+f"(d[22]), "+f"(d[23]), "+f"(d[24]), "+f"(d[25]), "+f"(d[26]), "+f"(d[27]), "+f"(d[28]), "+f"(d[29]), "+f"(d[30]), "+f"(d[31]), "+f"(d[32]), "+f"(d[33]), "+f"(d[34]), "+f"(d[35]), "+f"(d[36]), "+f"(d[37]), "+f"(d[38]), "+f"(d[39]), "+f"(d[40]), "+f"(d[41]), "+f"(d[42]), "+f"(d[43]), "+f"(d[44]), "+f"(d[45]), "+f"(d[46]), "+f"(d[47]), "+f"(d[48]), "+f"(d[49]), "+f"(d[50]), "+f"(d[51]), "+f"(d[52]), "+f"(d[53]), "+f"(d[54]), "+f"(d[55]), "+f"(d[56]), "+f"(d[57]), "+f"(d[58]), "+f"(d[59]), "+f"(d[60]), "+f"(d[61]), "+f"(d[62]), "+f"(d[63]) : "r"(da), "r"(db), "r"(sc), "n"(SA), "n"(SB), "n"(TA), "n"(TB), "n"(0x40000040));
  }
};
template<int N> struct WRS;
template<> struct WRS<8> {
  static __device__ __forceinline__ void run(float* d, uint32_t a0, uint32_t a1, uint32_t a2, uint32_t a3, uint64_t db, int sc) {
    asm volatile("{\n.reg .pred p;\nsetp.ne.b32 p, %9, 0;\nwgmma.mma_async.sync.aligned.m64n8k16.f32.bf16.bf16 {%0, %1, %2, %3}, {%4, %5, %6, %7}, %8, p, 1, 1, 0;\n}\n"
      : "+f"(d[0]), "+f"(d[1]), "+f"(d[2]), "+f"(d[3]) : "r"(a0), "r"(a1), "r"(a2), "r"(a3), "l"(db), "r"(sc));
  }
};
template<> struct WRS<16> {
  static __device__ __forceinline__ void run(float* d, uint32_t a0, uint32_t a1, uint32_t a2, uint32_t a3, uint64_t db, int sc) {
    asm volatile("{\n.reg .pred p;\nsetp.ne.b32 p, %13, 0;\nwgmma.mma_async.sync.aligned.m64n16k16.f32.bf16.bf16 {%0, %1, %2, %3, %4, %5, %6, %7}, {%8, %9, %10, %11}, %12, p, 1, 1, 0;\n}\n"
      : "+f"(d[0]), "+f"(d[1]), "+f"(d[2]), "+f"(d[3]), "+f"(d[4]), "+f"(d[5]), "+f"(d[6]), "+f"(d[7]) : "r"(a0), "r"(a1), "r"(a2), "r"(a3), "l"(db), "r"(sc));
  }
};
template<> struct WRS<24> {
  static __device__ __forceinline__ void run(float* d, uint32_t a0, uint32_t a1, uint32_t a2, uint32_t a3, uint64_t db, int sc) {
    asm volatile("{\n.reg .pred p;\nsetp.ne.b32 p, %17, 0;\nwgmma.mma_async.sync.aligned.m64n24k16.f32.bf16.bf16 {%0, %1, %2, %3, %4, %5, %6, %7, %8, %9, %10, %11}, {%12, %13, %14, %15}, %16, p, 1, 1, 0;\n}\n"
      : "+f"(d[0]), "+f"(d[1]), "+f"(d[2]), "+f"(d[3]), "+f"(d[4]), "+f"(d[5]), "+f"(d[6]), "+f"(d[7]), "+f"(d[8]), "+f"(d[9]), "+f"(d[10]), "+f"(d[11]) : "r"(a0), "r"(a1), "r"(a2), "r"(a3), "l"(db), "r"(sc));
  }
};
template<> struct WRS<32> {
  static __device__ __forceinline__ void run(float* d, uint32_t a0, uint32_t a1, uint32_t a2, uint32_t a3, uint64_t db, int sc) {
    asm volatile("{\n.reg .pred p;\nsetp.ne.b32 p, %21, 0;\nwgmma.mma_async.sync.aligned.m64n32k16.f32.bf16.bf16 {%0, %1, %2, %3, %4, %5, %6, %7, %8, %9, %10, %11, %12, %13, %14, %15}, {%16, %17, %18, %19}, %20, p, 1, 1, 0;\n}\n"
      : "+f"(d[0]), "+f"(d[1]), "+f"(d[2]), "+f"(d[3]), "+f"(d[4]), "+f"(d[5]), "+f"(d[6]), "+f"(d[7]), "+f"(d[8]), "+f"(d[9]), "+f"(d[10]), "+f"(d[11]), "+f"(d[12]), "+f"(d[13]), "+f"(d[14]), "+f"(d[15]) : "r"(a0), "r"(a1), "r"(a2), "r"(a3), "l"(db), "r"(sc));
  }
};
template<> struct WRS<40> {
  static __device__ __forceinline__ void run(float* d, uint32_t a0, uint32_t a1, uint32_t a2, uint32_t a3, uint64_t db, int sc) {
    asm volatile("{\n.reg .pred p;\nsetp.ne.b32 p, %25, 0;\nwgmma.mma_async.sync.aligned.m64n40k16.f32.bf16.bf16 {%0, %1, %2, %3, %4, %5, %6, %7, %8, %9, %10, %11, %12, %13, %14, %15, %16, %17, %18, %19}, {%20, %21, %22, %23}, %24, p, 1, 1, 0;\n}\n"
      : "+f"(d[0]), "+f"(d[1]), "+f"(d[2]), "+f"(d[3]), "+f"(d[4]), "+f"(d[5]), "+f"(d[6]), "+f"(d[7]), "+f"(d[8]), "+f"(d[9]), "+f"(d[10]), "+f"(d[11]), "+f"(d[12]), "+f"(d[13]), "+f"(d[14]), "+f"(d[15]), "+f"(d[16]), "+f"(d[17]), "+f"(d[18]), "+f"(d[19]) : "r"(a0), "r"(a1), "r"(a2), "r"(a3), "l"(db), "r"(sc));
  }
};
template<> struct WRS<48> {
  static __device__ __forceinline__ void run(float* d, uint32_t a0, uint32_t a1, uint32_t a2, uint32_t a3, uint64_t db, int sc) {
    asm volatile("{\n.reg .pred p;\nsetp.ne.b32 p, %29, 0;\nwgmma.mma_async.sync.aligned.m64n48k16.f32.bf16.bf16 {%0, %1, %2, %3, %4, %5, %6, %7, %8, %9, %10, %11, %12, %13, %14, %15, %16, %17, %18, %19, %20, %21, %22, %23}, {%24, %25, %26, %27}, %28, p, 1, 1, 0;\n}\n"
      : "+f"(d[0]), "+f"(d[1]), "+f"(d[2]), "+f"(d[3]), "+f"(d[4]), "+f"(d[5]), "+f"(d[6]), "+f"(d[7]), "+f"(d[8]), "+f"(d[9]), "+f"(d[10]), "+f"(d[11]), "+f"(d[12]), "+f"(d[13]), "+f"(d[14]), "+f"(d[15]), "+f"(d[16]), "+f"(d[17]), "+f"(d[18]), "+f"(d[19]), "+f"(d[20]), "+f"(d[21]), "+f"(d[22]), "+f"(d[23]) : "r"(a0), "r"(a1), "r"(a2), "r"(a3), "l"(db), "r"(sc));
  }
};
template<> struct WRS<56> {
  static __device__ __forceinline__ void run(float* d, uint32_t a0, uint32_t a1, uint32_t a2, uint32_t a3, uint64_t db, int sc) {
    asm volatile("{\n.reg .pred p;\nsetp.ne.b32 p, %33, 0;\nwgmma.mma_async.sync.aligned.m64n56k16.f32.bf16.bf16 {%0, %1, %2, %3, %4, %5, %6, %7, %8, %9, %10, %11, %12, %13, %14, %15, %16, %17, %18, %19, %20, %21, %22, %23, %24, %25, %26, %27}, {%28, %29, %30, %31}, %32, p, 1, 1, 0;\n}\n"
      : "+f"(d[0]), "+f"(d[1]), "+f"(d[2]), "+f"(d[3]), "+f"(d[4]), "+f"(d[5]), "+f"(d[6]), "+f"(d[7]), "+f"(d[8]), "+f"(d[9]), "+f"(d[10]), "+f"(d[11]), "+f"(d[12]), "+f"(d[13]), "+f"(d[14]), "+f"(d[15]), "+f"(d[16]), "+f"(d[17]), "+f"(d[18]), "+f"(d[19]), "+f"(d[20]), "+f"(d[21]), "+f"(d[22]), "+f"(d[23]), "+f"(d[24]), "+f"(d[25]), "+f"(d[26]), "+f"(d[27]) : "r"(a0), "r"(a1), "r"(a2), "r"(a3), "l"(db), "r"(sc));
  }
};
template<> struct WRS<64> {
  static __device__ __forceinline__ void run(float* d, uint32_t a0, uint32_t a1, uint32_t a2, uint32_t a3, uint64_t db, int sc) {
    asm volatile("{\n.reg .pred p;\nsetp.ne.b32 p, %37, 0;\nwgmma.mma_async.sync.aligned.m64n64k16.f32.bf16.bf16 {%0, %1, %2, %3, %4, %5, %6, %7, %8, %9, %10, %11, %12, %13, %14, %15, %16, %17, %18, %19, %20, %21, %22, %23, %24, %25, %26, %27, %28, %29, %30, %31}, {%32, %33, %34, %35}, %36, p, 1, 1, 0;\n}\n"
      : "+f"(d[0]), "+f"(d[1]), "+f"(d[2]), "+f"(d[3]), "+f"(d[4]), "+f"(d[5]), "+f"(d[6]), "+f"(d[7]), "+f"(d[8]), "+f"(d[9]), "+f"(d[10]), "+f"(d[11]), "+f"(d[12]), "+f"(d[13]), "+f"(d[14]), "+f"(d[15]), "+f"(d[16]), "+f"(d[17]), "+f"(d[18]), "+f"(d[19]), "+f"(d[20]), "+f"(d[21]), "+f"(d[22]), "+f"(d[23]), "+f"(d[24]), "+f"(d[25]), "+f"(d[26]), "+f"(d[27]), "+f"(d[28]), "+f"(d[29]), "+f"(d[30]), "+f"(d[31]) : "r"(a0), "r"(a1), "r"(a2), "r"(a3), "l"(db), "r"(sc));
  }
};
template<> struct WRS<72> {
  static __device__ __forceinline__ void run(float* d, uint32_t a0, uint32_t a1, uint32_t a2, uint32_t a3, uint64_t db, int sc) {
    asm volatile("{\n.reg .pred p;\nsetp.ne.b32 p, %41, 0;\nwgmma.mma_async.sync.aligned.m64n72k16.f32.bf16.bf16 {%0, %1, %2, %3, %4, %5, %6, %7, %8, %9, %10, %11, %12, %13, %14, %15, %16, %17, %18, %19, %20, %21, %22, %23, %24, %25, %26, %27, %28, %29, %30, %31, %32, %33, %34, %35}, {%36, %37, %38, %39}, %40, p, 1, 1, 0;\n}\n"
      : "+f"(d[0]), "+f"(d[1]), "+f"(d[2]), "+f"(d[3]), "+f"(d[4]), "+f"(d[5]), "+f"(d[6]), "+f"(d[7]), "+f"(d[8]), "+f"(d[9]), "+f"(d[10]), "+f"(d[11]), "+f"(d[12]), "+f"(d[13]), "+f"(d[14]), "+f"(d[15]), "+f"(d[16]), "+f"(d[17]), "+f"(d[18]), "+f"(d[19]), "+f"(d[20]), "+f"(d[21]), "+f"(d[22]), "+f"(d[23]), "+f"(d[24]), "+f"(d[25]), "+f"(d[26]), "+f"(d[27]), "+f"(d[28]), "+f"(d[29]), "+f"(d[30]), "+f"(d[31]), "+f"(d[32]), "+f"(d[33]), "+f"(d[34]), "+f"(d[35]) : "r"(a0), "r"(a1), "r"(a2), "r"(a3), "l"(db), "r"(sc));
  }
};
template<> struct WRS<80> {
  static __device__ __forceinline__ void run(float* d, uint32_t a0, uint32_t a1, uint32_t a2, uint32_t a3, uint64_t db, int sc) {
    asm volatile("{\n.reg .pred p;\nsetp.ne.b32 p, %45, 0;\nwgmma.mma_async.sync.aligned.m64n80k16.f32.bf16.bf16 {%0, %1, %2, %3, %4, %5, %6, %7, %8, %9, %10, %11, %12, %13, %14, %15, %16, %17, %18, %19, %20, %21, %22, %23, %24, %25, %26, %27, %28, %29, %30, %31, %32, %33, %34, %35, %36, %37, %38, %39}, {%40, %41, %42, %43}, %44, p, 1, 1, 0;\n}\n"
      : "+f"(d[0]), "+f"(d[1]), "+f"(d[2]), "+f"(d[3]), "+f"(d[4]), "+f"(d[5]), "+f"(d[6]), "+f"(d[7]), "+f"(d[8]), "+f"(d[9]), "+f"(d[10]), "+f"(d[11]), "+f"(d[12]), "+f"(d[13]), "+f"(d[14]), "+f"(d[15]), "+f"(d[16]), "+f"(d[17]), "+f"(d[18]), "+f"(d[19]), "+f"(d[20]), "+f"(d[21]), "+f"(d[22]), "+f"(d[23]), "+f"(d[24]), "+f"(d[25]), "+f"(d[26]), "+f"(d[27]), "+f"(d[28]), "+f"(d[29]), "+f"(d[30]), "+f"(d[31]), "+f"(d[32]), "+f"(d[33]), "+f"(d[34]), "+f"(d[35]), "+f"(d[36]), "+f"(d[37]), "+f"(d[38]), "+f"(d[39]) : "r"(a0), "r"(a1), "r"(a2), "r"(a3), "l"(db), "r"(sc));
  }
};
template<> struct WRS<88> {
  static __device__ __forceinline__ void run(float* d, uint32_t a0, uint32_t a1, uint32_t a2, uint32_t a3, uint64_t db, int sc) {
    asm volatile("{\n.reg .pred p;\nsetp.ne.b32 p, %49, 0;\nwgmma.mma_async.sync.aligned.m64n88k16.f32.bf16.bf16 {%0, %1, %2, %3, %4, %5, %6, %7, %8, %9, %10, %11, %12, %13, %14, %15, %16, %17, %18, %19, %20, %21, %22, %23, %24, %25, %26, %27, %28, %29, %30, %31, %32, %33, %34, %35, %36, %37, %38, %39, %40, %41, %42, %43}, {%44, %45, %46, %47}, %48, p, 1, 1, 0;\n}\n"
      : "+f"(d[0]), "+f"(d[1]), "+f"(d[2]), "+f"(d[3]), "+f"(d[4]), "+f"(d[5]), "+f"(d[6]), "+f"(d[7]), "+f"(d[8]), "+f"(d[9]), "+f"(d[10]), "+f"(d[11]), "+f"(d[12]), "+f"(d[13]), "+f"(d[14]), "+f"(d[15]), "+f"(d[16]), "+f"(d[17]), "+f"(d[18]), "+f"(d[19]), "+f"(d[20]), "+f"(d[21]), "+f"(d[22]), "+f"(d[23]), "+f"(d[24]), "+f"(d[25]), "+f"(d[26]), "+f"(d[27]), "+f"(d[28]), "+f"(d[29]), "+f"(d[30]), "+f"(d[31]), "+f"(d[32]), "+f"(d[33]), "+f"(d[34]), "+f"(d[35]), "+f"(d[36]), "+f"(d[37]), "+f"(d[38]), "+f"(d[39]), "+f"(d[40]), "+f"(d[41]), "+f"(d[42]), "+f"(d[43]) : "r"(a0), "r"(a1), "r"(a2), "r"(a3), "l"(db), "r"(sc));
  }
};
template<> struct WRS<96> {
  static __device__ __forceinline__ void run(float* d, uint32_t a0, uint32_t a1, uint32_t a2, uint32_t a3, uint64_t db, int sc) {
    asm volatile("{\n.reg .pred p;\nsetp.ne.b32 p, %53, 0;\nwgmma.mma_async.sync.aligned.m64n96k16.f32.bf16.bf16 {%0, %1, %2, %3, %4, %5, %6, %7, %8, %9, %10, %11, %12, %13, %14, %15, %16, %17, %18, %19, %20, %21, %22, %23, %24, %25, %26, %27, %28, %29, %30, %31, %32, %33, %34, %35, %36, %37, %38, %39, %40, %41, %42, %43, %44, %45, %46, %47}, {%48, %49, %50, %51}, %52, p, 1, 1, 0;\n}\n"
      : "+f"(d[0]), "+f"(d[1]), "+f"(d[2]), "+f"(d[3]), "+f"(d[4]), "+f"(d[5]), "+f"(d[6]), "+f"(d[7]), "+f"(d[8]), "+f"(d[9]), "+f"(d[10]), "+f"(d[11]), "+f"(d[12]), "+f"(d[13]), "+f"(d[14]), "+f"(d[15]), "+f"(d[16]), "+f"(d[17]), "+f"(d[18]), "+f"(d[19]), "+f"(d[20]), "+f"(d[21]), "+f"(d[22]), "+f"(d[23]), "+f"(d[24]), "+f"(d[25]), "+f"(d[26]), "+f"(d[27]), "+f"(d[28]), "+f"(d[29]), "+f"(d[30]), "+f"(d[31]), "+f"(d[32]), "+f"(d[33]), "+f"(d[34]), "+f"(d[35]), "+f"(d[36]), "+f"(d[37]), "+f"(d[38]), "+f"(d[39]), "+f"(d[40]), "+f"(d[41]), "+f"(d[42]), "+f"(d[43]), "+f"(d[44]), "+f"(d[45]), "+f"(d[46]), "+f"(d[47]) : "r"(a0), "r"(a1), "r"(a2), "r"(a3), "l"(db), "r"(sc));
  }
};
template<> struct WRS<104> {
  static __device__ __forceinline__ void run(float* d, uint32_t a0, uint32_t a1, uint32_t a2, uint32_t a3, uint64_t db, int sc) {
    asm volatile("{\n.reg .pred p;\nsetp.ne.b32 p, %57, 0;\nwgmma.mma_async.sync.aligned.m64n104k16.f32.bf16.bf16 {%0, %1, %2, %3, %4, %5, %6, %7, %8, %9, %10, %11, %12, %13, %14, %15, %16, %17, %18, %19, %20, %21, %22, %23, %24, %25, %26, %27, %28, %29, %30, %31, %32, %33, %34, %35, %36, %37, %38, %39, %40, %41, %42, %43, %44, %45, %46, %47, %48, %49, %50, %51}, {%52, %53, %54, %55}, %56, p, 1, 1, 0;\n}\n"
      : "+f"(d[0]), "+f"(d[1]), "+f"(d[2]), "+f"(d[3]), "+f"(d[4]), "+f"(d[5]), "+f"(d[6]), "+f"(d[7]), "+f"(d[8]), "+f"(d[9]), "+f"(d[10]), "+f"(d[11]), "+f"(d[12]), "+f"(d[13]), "+f"(d[14]), "+f"(d[15]), "+f"(d[16]), "+f"(d[17]), "+f"(d[18]), "+f"(d[19]), "+f"(d[20]), "+f"(d[21]), "+f"(d[22]), "+f"(d[23]), "+f"(d[24]), "+f"(d[25]), "+f"(d[26]), "+f"(d[27]), "+f"(d[28]), "+f"(d[29]), "+f"(d[30]), "+f"(d[31]), "+f"(d[32]), "+f"(d[33]), "+f"(d[34]), "+f"(d[35]), "+f"(d[36]), "+f"(d[37]), "+f"(d[38]), "+f"(d[39]), "+f"(d[40]), "+f"(d[41]), "+f"(d[42]), "+f"(d[43]), "+f"(d[44]), "+f"(d[45]), "+f"(d[46]), "+f"(d[47]), "+f"(d[48]), "+f"(d[49]), "+f"(d[50]), "+f"(d[51]) : "r"(a0), "r"(a1), "r"(a2), "r"(a3), "l"(db), "r"(sc));
  }
};
template<> struct WRS<112> {
  static __device__ __forceinline__ void run(float* d, uint32_t a0, uint32_t a1, uint32_t a2, uint32_t a3, uint64_t db, int sc) {
    asm volatile("{\n.reg .pred p;\nsetp.ne.b32 p, %61, 0;\nwgmma.mma_async.sync.aligned.m64n112k16.f32.bf16.bf16 {%0, %1, %2, %3, %4, %5, %6, %7, %8, %9, %10, %11, %12, %13, %14, %15, %16, %17, %18, %19, %20, %21, %22, %23, %24, %25, %26, %27, %28, %29, %30, %31, %32, %33, %34, %35, %36, %37, %38, %39, %40, %41, %42, %43, %44, %45, %46, %47, %48, %49, %50, %51, %52, %53, %54, %55}, {%56, %57, %58, %59}, %60, p, 1, 1, 0;\n}\n"
      : "+f"(d[0]), "+f"(d[1]), "+f"(d[2]), "+f"(d[3]), "+f"(d[4]), "+f"(d[5]), "+f"(d[6]), "+f"(d[7]), "+f"(d[8]), "+f"(d[9]), "+f"(d[10]), "+f"(d[11]), "+f"(d[12]), "+f"(d[13]), "+f"(d[14]), "+f"(d[15]), "+f"(d[16]), "+f"(d[17]), "+f"(d[18]), "+f"(d[19]), "+f"(d[20]), "+f"(d[21]), "+f"(d[22]), "+f"(d[23]), "+f"(d[24]), "+f"(d[25]), "+f"(d[26]), "+f"(d[27]), "+f"(d[28]), "+f"(d[29]), "+f"(d[30]), "+f"(d[31]), "+f"(d[32]), "+f"(d[33]), "+f"(d[34]), "+f"(d[35]), "+f"(d[36]), "+f"(d[37]), "+f"(d[38]), "+f"(d[39]), "+f"(d[40]), "+f"(d[41]), "+f"(d[42]), "+f"(d[43]), "+f"(d[44]), "+f"(d[45]), "+f"(d[46]), "+f"(d[47]), "+f"(d[48]), "+f"(d[49]), "+f"(d[50]), "+f"(d[51]), "+f"(d[52]), "+f"(d[53]), "+f"(d[54]), "+f"(d[55]) : "r"(a0), "r"(a1), "r"(a2), "r"(a3), "l"(db), "r"(sc));
  }
};
template<> struct WRS<120> {
  static __device__ __forceinline__ void run(float* d, uint32_t a0, uint32_t a1, uint32_t a2, uint32_t a3, uint64_t db, int sc) {
    asm volatile("{\n.reg .pred p;\nsetp.ne.b32 p, %65, 0;\nwgmma.mma_async.sync.aligned.m64n120k16.f32.bf16.bf16 {%0, %1, %2, %3, %4, %5, %6, %7, %8, %9, %10, %11, %12, %13, %14, %15, %16, %17, %18, %19, %20, %21, %22, %23, %24, %25, %26, %27, %28, %29, %30, %31, %32, %33, %34, %35, %36, %37, %38, %39, %40, %41, %42, %43, %44, %45, %46, %47, %48, %49, %50, %51, %52, %53, %54, %55, %56, %57, %58, %59}, {%60, %61, %62, %63}, %64, p, 1, 1, 0;\n}\n"
      : "+f"(d[0]), "+f"(d[1]), "+f"(d[2]), "+f"(d[3]), "+f"(d[4]), "+f"(d[5]), "+f"(d[6]), "+f"(d[7]), "+f"(d[8]), "+f"(d[9]), "+f"(d[10]), "+f"(d[11]), "+f"(d[12]), "+f"(d[13]), "+f"(d[14]), "+f"(d[15]), "+f"(d[16]), "+f"(d[17]), "+f"(d[18]), "+f"(d[19]), "+f"(d[20]), "+f"(d[21]), "+f"(d[22]), "+f"(d[23]), "+f"(d[24]), "+f"(d[25]), "+f"(d[26]), "+f"(d[27]), "+f"(d[28]), "+f"(d[29]), "+f"(d[30]), "+f"(d[31]), "+f"(d[32]), "+f"(d[33]), "+f"(d[34]), "+f"(d[35]), "+f"(d[36]), "+f"(d[37]), "+f"(d[38]), "+f"(d[39]), "+f"(d[40]), "+f"(d[41]), "+f"(d[42]), "+f"(d[43]), "+f"(d[44]), "+f"(d[45]), "+f"(d[46]), "+f"(d[47]), "+f"(d[48]), "+f"(d[49]), "+f"(d[50]), "+f"(d[51]), "+f"(d[52]), "+f"(d[53]), "+f"(d[54]), "+f"(d[55]), "+f"(d[56]), "+f"(d[57]), "+f"(d[58]), "+f"(d[59]) : "r"(a0), "r"(a1), "r"(a2), "r"(a3), "l"(db), "r"(sc));
  }
};
template<> struct WRS<128> {
  static __device__ __forceinline__ void run(float* d, uint32_t a0, uint32_t a1, uint32_t a2, uint32_t a3, uint64_t db, int sc) {
    asm volatile("{\n.reg .pred p;\nsetp.ne.b32 p, %69, 0;\nwgmma.mma_async.sync.aligned.m64n128k16.f32.bf16.bf16 {%0, %1, %2, %3, %4, %5, %6, %7, %8, %9, %10, %11, %12, %13, %14, %15, %16, %17, %18, %19, %20, %21, %22, %23, %24, %25, %26, %27, %28, %29, %30, %31, %32, %33, %34, %35, %36, %37, %38, %39, %40, %41, %42, %43, %44, %45, %46, %47, %48, %49, %50, %51, %52, %53, %54, %55, %56, %57, %58, %59, %60, %61, %62, %63}, {%64, %65, %66, %67}, %68, p, 1, 1, 0;\n}\n"
      : "+f"(d[0]), "+f"(d[1]), "+f"(d[2]), "+f"(d[3]), "+f"(d[4]), "+f"(d[5]), "+f"(d[6]), "+f"(d[7]), "+f"(d[8]), "+f"(d[9]), "+f"(d[10]), "+f"(d[11]), "+f"(d[12]), "+f"(d[13]), "+f"(d[14]), "+f"(d[15]), "+f"(d[16]), "+f"(d[17]), "+f"(d[18]), "+f"(d[19]), "+f"(d[20]), "+f"(d[21]), "+f"(d[22]), "+f"(d[23]), "+f"(d[24]), "+f"(d[25]), "+f"(d[26]), "+f"(d[27]), "+f"(d[28]), "+f"(d[29]), "+f"(d[30]), "+f"(d[31]), "+f"(d[32]), "+f"(d[33]), "+f"(d[34]), "+f"(d[35]), "+f"(d[36]), "+f"(d[37]), "+f"(d[38]), "+f"(d[39]), "+f"(d[40]), "+f"(d[41]), "+f"(d[42]), "+f"(d[43]), "+f"(d[44]), "+f"(d[45]), "+f"(d[46]), "+f"(d[47]), "+f"(d[48]), "+f"(d[49]), "+f"(d[50]), "+f"(d[51]), "+f"(d[52]), "+f"(d[53]), "+f"(d[54]), "+f"(d[55]), "+f"(d[56]), "+f"(d[57]), "+f"(d[58]), "+f"(d[59]), "+f"(d[60]), "+f"(d[61]), "+f"(d[62]), "+f"(d[63]) : "r"(a0), "r"(a1), "r"(a2), "r"(a3), "l"(db), "r"(sc));
  }
};

__device__ unsigned int g_ticket;
__device__ unsigned int g_flag[16 * 32];
__device__ unsigned long long g_E[16 * 640];
__device__ uint4 g_H[16 * 20 * 1024];

#define STAMP(i)
#define STAMPG(i)
#define PROF_ARG
#define PROF_PASS

struct Params {
  CUtensorMap x, bre, bim, cre, cim, k, v, k16, v16, q, oa, ob, oh, o4;
  const __nv_bfloat16 *xp, *lre, *lim, *logdt, *dskip, *brep, *bimp, *kp, *vp, *shk, *ssmk, *ssmd;
  float* out;
  uint32_t zero;
};

__device__ __forceinline__ uint32_t smem_u32(const void* p) { return (uint32_t)__cvta_generic_to_shared(p); }
__device__ __forceinline__ uint32_t mkdesc(uint32_t addr, uint32_t lbo) { return ((addr & 0x3FFFF) >> 4) | ((lbo >> 4) << 16); }
__device__ __forceinline__ void wg_fence() { asm volatile("wgmma.fence.sync.aligned;" ::: "memory"); }
__device__ __forceinline__ void wg_commit() { asm volatile("wgmma.commit_group.sync.aligned;" ::: "memory"); }
template <int N> __device__ __forceinline__ void wg_wait() { asm volatile("wgmma.wait_group.sync.aligned %0;" ::"n"(N) : "memory"); }
__device__ __forceinline__ void mbar_init(uint32_t bar, int cnt) { asm volatile("mbarrier.init.shared::cta.b64 [%0], %1;" ::"r"(bar), "r"(cnt) : "memory"); }
__device__ __forceinline__ void mbar_expect(uint32_t bar, uint32_t bytes) {
  asm volatile("mbarrier.arrive.expect_tx.shared::cta.b64 _, [%0], %1;" ::"r"(bar), "r"(bytes) : "memory");
}
__device__ __forceinline__ void mbar_arrive(uint32_t bar) { asm volatile("mbarrier.arrive.shared::cta.b64 _, [%0];" ::"r"(bar) : "memory"); }
__device__ __forceinline__ void mbar_wait(uint32_t bar, uint32_t parity) {
  asm volatile(
      "{\n.reg .pred p;\n.reg .u32 c;\nmov.u32 c, 0;\n"
      "L1_%=:\nmbarrier.try_wait.parity.shared::cta.b64 p, [%0], %1;\n@p bra L2_%=;\n"
      "add.u32 c, c, 1;\nsetp.lt.u32 p, c, 2000000;\n@p bra L1_%=;\ntrap;\nL2_%=:\n}" ::"r"(bar), "r"(parity) : "memory");
}
__device__ __forceinline__ void tma2d(uint32_t dst, const CUtensorMap* m, int c0, int c1, uint32_t bar) {
  asm volatile("cp.async.bulk.tensor.2d.shared::cluster.global.mbarrier::complete_tx::bytes [%0], [%1, {%3, %4}], [%2];" ::"r"(dst),
               "l"(m), "r"(bar), "r"(c0), "r"(c1) : "memory");
}
__device__ __forceinline__ void tma3d(uint32_t dst, const CUtensorMap* m, int c0, int c1, int c2, uint32_t bar) {
  asm volatile("cp.async.bulk.tensor.3d.shared::cluster.global.mbarrier::complete_tx::bytes [%0], [%1, {%3, %4, %5}], [%2];" ::"r"(dst),
               "l"(m), "r"(bar), "r"(c0), "r"(c1), "r"(c2) : "memory");
}
__device__ __forceinline__ void tma5d(uint32_t dst, const CUtensorMap* m, int c0, int c4, uint32_t bar) {
  asm volatile("cp.async.bulk.tensor.5d.shared::cluster.global.mbarrier::complete_tx::bytes [%0], [%1, {%3, %4, %4, %4, %5}], [%2];" ::"r"(dst),
               "l"(m), "r"(bar), "r"(c0), "r"(0), "r"(c4) : "memory");
}
__device__ __forceinline__ void tma5d_store(const CUtensorMap* m, uint32_t src, int c0, int c3, int c4) {
  asm volatile("cp.async.bulk.tensor.5d.global.shared::cta.bulk_group [%0, {%2, %3, %3, %4, %5}], [%1];" ::"l"(m), "r"(src), "r"(c0), "r"(0), "r"(c3), "r"(c4) : "memory");
}
__device__ __forceinline__ void bulk_g2s(uint32_t dst, const void* src, uint32_t bytes, uint32_t bar) {
  asm volatile("cp.async.bulk.shared::cluster.global.mbarrier::complete_tx::bytes [%0], [%1], %2, [%3];" ::"r"(dst), "l"(src), "r"(bytes), "r"(bar) : "memory");
}
__device__ __forceinline__ void bulk_s2g(void* dst, uint32_t src, uint32_t bytes) {
  asm volatile("cp.async.bulk.global.shared::cta.bulk_group [%0], [%1], %2;" ::"l"(dst), "r"(src), "r"(bytes) : "memory");
}
__device__ __forceinline__ void prefetch_tmap(const CUtensorMap* m) { asm volatile("prefetch.tensormap [%0];" ::"l"(m) : "memory"); }
__device__ __forceinline__ void fence_async_smem() { asm volatile("fence.proxy.async.shared::cta;" ::: "memory"); }
__device__ __forceinline__ void bar_sync(int id, int n) { asm volatile("bar.sync %0, %1;" ::"r"(id), "r"(n) : "memory"); }
__device__ __forceinline__ void bar_arrive(int id, int n) { asm volatile("bar.arrive %0, %1;" ::"r"(id), "r"(n) : "memory"); }
__device__ __forceinline__ uint2 lds64(uint32_t a) { uint2 r; asm volatile("ld.shared.v2.u32 {%0,%1}, [%2];" : "=r"(r.x), "=r"(r.y) : "r"(a) : "memory"); return r; }
__device__ __forceinline__ uint32_t pack_bf16(float lo, float hi) {
  uint32_t r; asm("cvt.rn.bf16x2.f32 %0, %1, %2;" : "=r"(r) : "f"(hi), "f"(lo)); return r;
}
__device__ __forceinline__ uint32_t bmul2(uint32_t a, uint32_t b) { uint32_t r; asm("mul.rn.bf16x2 %0, %1, %2;" : "=r"(r) : "r"(a), "r"(b)); return r; }
__device__ __forceinline__ uint32_t badd2(uint32_t a, uint32_t b) { uint32_t r; asm("add.rn.bf16x2 %0, %1, %2;" : "=r"(r) : "r"(a), "r"(b)); return r; }
__device__ __forceinline__ float bf_lo(uint32_t v) { return __uint_as_float(v << 16); }
__device__ __forceinline__ float bf_hi(uint32_t v) { return __uint_as_float(v & 0xffff0000u); }
__device__ __forceinline__ void stsm4(uint32_t a, uint32_t r0, uint32_t r1, uint32_t r2, uint32_t r3) {
  asm volatile("stmatrix.sync.aligned.m8n8.x4.shared.b16 [%0], {%1,%2,%3,%4};" ::"r"(a), "r"(r0), "r"(r1), "r"(r2), "r"(r3) : "memory");
}
__device__ __forceinline__ void stsm4t(uint32_t a, uint32_t r0, uint32_t r1, uint32_t r2, uint32_t r3) {
  asm volatile("stmatrix.sync.aligned.m8n8.x4.trans.shared.b16 [%0], {%1,%2,%3,%4};" ::"r"(a), "r"(r0), "r"(r1), "r"(r2), "r"(r3) : "memory");
}
__device__ __forceinline__ void ldsm4(uint32_t a, uint32_t* r) {
  asm volatile("ldmatrix.sync.aligned.m8n8.x4.shared.b16 {%0,%1,%2,%3}, [%4];" : "=r"(r[0]), "=r"(r[1]), "=r"(r[2]), "=r"(r[3]) : "r"(a) : "memory");
}
__device__ __forceinline__ void ldsm4t(uint32_t a, uint32_t* r) {
  asm volatile("ldmatrix.sync.aligned.m8n8.x4.trans.shared.b16 {%0,%1,%2,%3}, [%4];" : "=r"(r[0]), "=r"(r[1]), "=r"(r[2]), "=r"(r[3]) : "r"(a) : "memory");
}
__device__ __forceinline__ uint32_t lds32(uint32_t a) { uint32_t r; asm volatile("ld.shared.u32 %0, [%1];" : "=r"(r) : "r"(a) : "memory"); return r; }
__device__ __forceinline__ float2 lds64f(uint32_t a) { float2 r; asm volatile("ld.shared.v2.f32 {%0,%1}, [%2];" : "=f"(r.x), "=f"(r.y) : "r"(a) : "memory"); return r; }
__device__ __forceinline__ uint4 lds128(uint32_t a) {
  uint4 r; asm volatile("ld.shared.v4.u32 {%0,%1,%2,%3}, [%4];" : "=r"(r.x), "=r"(r.y), "=r"(r.z), "=r"(r.w) : "r"(a) : "memory"); return r;
}
__device__ __forceinline__ void sts32(uint32_t a, uint32_t v) { asm volatile("st.shared.u32 [%0], %1;" ::"r"(a), "r"(v) : "memory"); }
__device__ __forceinline__ void sts64f(uint32_t a, float x, float y) { asm volatile("st.shared.v2.f32 [%0], {%1,%2};" ::"r"(a), "f"(x), "f"(y) : "memory"); }
__device__ __forceinline__ void sts128(uint32_t a, uint32_t x, uint32_t y, uint32_t z, uint32_t w) {
  asm volatile("st.shared.v4.u32 [%0], {%1,%2,%3,%4};" ::"r"(a), "r"(x), "r"(y), "r"(z), "r"(w) : "memory");
}
__device__ __forceinline__ float bf2f(const __nv_bfloat16* p) { return __bfloat162float(*p); }
template <int N> __device__ __forceinline__ void fence_regs(float* a) {
#pragma unroll
  for (int i = 0; i < N; i++) asm volatile("" : "+f"(a[i])::"memory");
}
struct cf { float r, i; };
__device__ __forceinline__ cf cmul(cf a, cf b) { cf o; o.r = a.r * b.r - a.i * b.i; o.i = a.r * b.i + a.i * b.r; return o; }
__device__ __forceinline__ cf cfma(cf a, cf b, cf c) {
  cf o; o.r = fmaf(a.r, b.r, fmaf(-a.i, b.i, c.r)); o.i = fmaf(a.r, b.i, fmaf(a.i, b.r, c.i)); return o;
}
__device__ __forceinline__ cf cshfl_up(cf a, int d) { cf o; o.r = __shfl_up_sync(0xffffffffu, a.r, d, 4); o.i = __shfl_up_sync(0xffffffffu, a.i, d, 4); return o; }
__device__ __forceinline__ uint32_t mapa(uint32_t addr, uint32_t rank) {
  uint32_t r; asm volatile("mapa.shared::cluster.u32 %0, %1, %2;" : "=r"(r) : "r"(addr), "r"(rank)); return r;
}
__device__ __forceinline__ void mbar_arrive_cluster(uint32_t bar) { asm volatile("mbarrier.arrive.shared::cluster.b64 _, [%0];" ::"r"(bar) : "memory"); }
__device__ __forceinline__ void tma2d_mc(uint32_t dst, const CUtensorMap* m, int c0, int c1, uint32_t bar) {
  asm volatile("cp.async.bulk.tensor.2d.shared::cluster.global.mbarrier::complete_tx::bytes.multicast::cluster [%0], [%1, {%3, %4}], [%2], %5;" ::"r"(dst),
               "l"(m), "r"(bar), "r"(c0), "r"(c1), "h"((uint16_t)3) : "memory");
}
__device__ __forceinline__ void sts128_cluster(uint32_t a, uint32_t x, uint32_t y, uint32_t z, uint32_t w) {
  asm volatile("st.shared::cluster.v4.u32 [%0], {%1,%2,%3,%4};" ::"r"(a), "r"(x), "r"(y), "r"(z), "r"(w) : "memory");
}
__device__ __forceinline__ void cluster_arrive_relaxed() { asm volatile("barrier.cluster.arrive.relaxed.aligned;" ::: "memory"); }
__device__ __forceinline__ void cluster_arrive_release() { asm volatile("barrier.cluster.arrive.release.aligned;" ::: "memory"); }
__device__ __forceinline__ void cluster_wait() { asm volatile("barrier.cluster.wait.acquire.aligned;" ::: "memory"); }
__device__ __forceinline__ void sts128f(uint32_t a, float x, float y, float z, float w) {
  asm volatile("st.shared.v4.f32 [%0], {%1,%2,%3,%4};" ::"r"(a), "f"(x), "f"(y), "f"(z), "f"(w) : "memory");
}

constexpr uint32_t SLOT = 16384;
constexpr uint32_t A_BAR = 14 * SLOT;
constexpr uint32_t A_G1F = A_BAR, A_G1E = A_BAR + 32, A_CF = A_BAR + 64, A_CE = A_BAR + 96, A_HF = A_BAR + 128, A_HE = A_BAR + 160,
                   A_G1D = A_BAR + 192, A_EPB = A_BAR + 200, A_XF = A_BAR + 208, A_HS = A_BAR + 216  , A_TKB = A_BAR + 248,
                   A_EPV = A_BAR + 256, A_HD = A_BAR + 264, A_SB = A_BAR + 272  , A_DSK = A_BAR + 288  ,
                   A_TAB = A_BAR + 544;
__host__ __device__ constexpr uint32_t cslot(int i) { return (6 + i) * SLOT; }
__host__ __device__ constexpr uint32_t hslot(int i) { return (i < 2 ? 10 + i : (i - 2) * 3) * SLOT; }

__device__ __forceinline__ void a_issue_stage(const Params& P, uint32_t sb, int kb, int pg, int tt) {
  const int s = kb & 3;
  const uint32_t bar = sb + A_G1F + 8 * s, st = sb + 3 * s * SLOT;
  mbar_expect(bar, 3 * SLOT);
  tma5d(st, &P.x, kb * 64, tt, bar);
  tma2d(st + SLOT, &P.bre, kb * 64, pg * 128, bar);
  tma2d(st + 2 * SLOT, &P.bim, kb * 64, pg * 128, bar);
}
__device__ __forceinline__ int k2_block(int ci, int pg) {
  if (ci < 4) return pg * 4 + ci;
  int g = pg + 1 + (ci & 3); if (g >= 5) g -= 5;
  return g * 4 + ((ci - 4) >> 2);
}

__device__ __forceinline__ void roleA_prod(const Params& P, uint32_t sb, int cta PROF_ARG) {
  const int tid = threadIdx.x, warp = __shfl_sync(0xffffffffu, tid >> 5, 0), lane = tid & 31;
  const int pg = cta >> 4, tt = cta & 15, rank = cta & 1;
  {
    asm volatile("setmaxnreg.dec.sync.aligned.u32 88;");
    if (warp == 8) {
      if (lane == 0) { a_issue_stage(P, sb, 2, pg, tt); a_issue_stage(P, sb, 3, pg, tt); STAMP(26); }
    }
    if (warp == 9 && lane == 0) {
      for (int i = 0; i < 4; i++) {
        mbar_init(sb + A_G1E + 8 * i, 2);
        mbar_init(sb + A_CF + 8 * i, 1); mbar_init(sb + A_CE + 8 * i, 4);
        mbar_init(sb + A_HF + 8 * i, 1); mbar_init(sb + A_HE + 8 * i, 2);
        mbar_init(sb + A_HS + 8 * i, 128);
      }
      mbar_init(sb + A_G1D, 256); mbar_init(sb + A_EPB, 64); mbar_init(sb + A_XF, 1); mbar_init(sb + A_TKB, 1); mbar_init(sb + A_HD, 2);
      mbar_init(sb + A_SB, 32); mbar_init(sb + A_SB + 8, 32);
      asm volatile("fence.mbarrier_init.release.cluster;" ::: "memory");
    }
    __syncwarp();
    cluster_arrive_relaxed();
    if (warp != 8) bar_sync(0, 384);
    if (warp == 8) {
      cluster_wait();
      for (int kb = 4; kb < 10; kb++) {
        const int s = kb & 3;
        mbar_wait(sb + A_G1E + 8 * s, ((kb >> 2) - 1) & 1);
        if (lane == 0) a_issue_stage(P, sb, kb, pg, tt);
        __syncwarp();
      }
      if (lane == 0) {
        mbar_expect(sb + A_XF, 2 * SLOT);
        tma5d(sb + 12 * SLOT, &P.x, pg * 128, tt, sb + A_XF);
        tma5d(sb + 13 * SLOT, &P.x, pg * 128 + 64, tt, sb + A_XF);
      }
      __syncwarp();
      for (int ci = 0; ci < 20; ci++) {
        const int ring = ci & 3;
        mbar_wait(sb + A_CE + 8 * ring, (ci >> 2) & 1);
        if (lane == 0) {
          const int blk = k2_block(ci, pg);
          const uint32_t bar = sb + A_CF + 8 * ring;
          mbar_expect(bar, SLOT);
          tma2d_mc(sb + cslot(ring) + rank * 8192, (blk & 1) ? &P.cim : &P.cre, (blk >> 1) * 64, pg * 128 + rank * 64, bar);
        }
        __syncwarp();
      }
    } else if (warp == 9) {
      cluster_wait();
      mbar_wait(sb + A_TKB, 0);
      const uint32_t epoch = lds32(sb + A_EPV);
      mbar_wait(sb + A_G1D, 0);
      uint32_t ready = 0;
      const unsigned int* fp = &g_flag[tt * 32 + lane];
      for (int hi = 0; hi < 16; hi++) {
        const int ring = hi & 3, blk = k2_block(hi + 4, pg);
        int it = 0;
        while (!((ready >> blk) & 1)) {
          uint32_t v;
          asm volatile("ld.relaxed.gpu.global.u32 %0, [%1];" : "=r"(v) : "l"(fp) : "memory");
          ready = __ballot_sync(0xffffffffu, v == epoch);
          if (++it > 4000000) asm volatile("trap;");
        }
        if (it) asm volatile("fence.proxy.async.global;" ::: "memory");
        if (hi == 0 && lane == 0) STAMP(11);
        if (hi >= 4) mbar_wait(sb + A_HE + 8 * ring, ((hi >> 2) - 1) & 1);
        if (lane == 0) {
          const uint32_t bar = sb + A_HF + 8 * ring;
          mbar_expect(bar, SLOT);
          bulk_g2s(sb + hslot(ring), (const uint8_t*)g_H + (size_t)(tt * 20 + blk) * SLOT, SLOT, bar);
        }
        __syncwarp();
      }
    } else {
      const int w = warp - 10;
      if (w == 0 && lane == 0) {
        const uint32_t tk = atomicAdd(&g_ticket, 1u);
        sts32(sb + A_EPV, tk / NA + 1);
        mbar_arrive(sb + A_TKB);
        prefetch_tmap(&P.cre); prefetch_tmap(&P.cim); prefetch_tmap(&P.oa);
      }
      __syncwarp();
      sts32(sb + A_DSK + (w * 32 + lane) * 4, __ldg((const uint32_t*)P.dskip + pg * 64 + w * 32 + lane));
      cf L128[2];
#pragma unroll
      for (int z = 0; z < 2; z++) {
        const int pl = w * 64 + 2 * lane + z, p = pg * 128 + pl;
        const float lr = bf2f(P.lre + p), li = bf2f(P.lim + p);
        const float dt = __bfloat162float(__float2bfloat16_rn(expf(bf2f(P.logdt + p))));
        const float e = expf(dt * lr);
        float sn, cs; sincosf(dt * li, &sn, &cs);
        cf L; L.r = e * cs; L.i = e * sn;
        const float nr = L.r - 1.0f, den = 2.0f / (lr * lr + li * li);
        sts128f(sb + A_TAB + pl * 16, L.r, L.i, (nr * lr + L.i * li) * den, (L.i * lr - nr * li) * den);
#pragma unroll
        for (int i = 0; i < 7; i++) L = cmul(L, L);
        L128[z] = L;
      }
      cluster_wait();
      mbar_wait(sb + A_TKB, 0);
      const uint32_t epoch = lds32(sb + A_EPV);
      unsigned long long* ep = &g_E[pg * 128 + w * 64 + 2 * lane];
      unsigned int* fp = &g_flag[tt * 32 + pg * 4 + w * 2];
      if (tt < 15) {
        const uint32_t pe = epoch - 1;
        const unsigned long long v = ((unsigned long long)((pe >> 4) & 15u) << 32) | (pe & 15u);
        asm volatile("st.relaxed.gpu.global.v2.u64 [%0], {%1, %1};" ::"l"(ep + tt * 640), "l"(v) : "memory");
      }
      if (lane == 0) asm volatile("st.relaxed.gpu.global.v2.u32 [%0], {%1, %1};" ::"l"(fp), "r"(epoch - 1) : "memory");
      mbar_arrive(sb + A_EPB);
      mbar_wait(sb + A_G1D, 0);
      {
        const unsigned long long want = ((unsigned long long)((epoch >> 4) & 15u) << 32) | (epoch & 15u), tmask = 0x0000000f0000000full;
        unsigned long long e0[15], e1[15];
        int it = 0;
        bool ok;
        do {
          unsigned long long bad = 0;
#pragma unroll
          for (int c = 0; c < 15; c++) {
            e0[c] = want; e1[c] = want;
            if (c < tt) asm volatile("ld.relaxed.gpu.global.v2.u64 {%0, %1}, [%2];" : "=l"(e0[c]), "=l"(e1[c]) : "l"(ep + c * 640) : "memory");
          }
#pragma unroll
          for (int c = 0; c < 15; c++) bad |= (e0[c] ^ want) | (e1[c] ^ want);
          ok = __all_sync(0xffffffffu, (bad & tmask) == 0);
          if (++it > 2000000) asm volatile("trap;");
        } while (!ok);
        cf s0, s1; s0.r = s0.i = s1.r = s1.i = 0.f;
#pragma unroll
        for (int c = 0; c < 15; c++) {
          if (c < tt) {
            cf b; b.r = __uint_as_float((uint32_t)e0[c]); b.i = __uint_as_float((uint32_t)(e0[c] >> 32));
            s0 = cfma(L128[0], s0, b);
            b.r = __uint_as_float((uint32_t)e1[c]); b.i = __uint_as_float((uint32_t)(e1[c] >> 32));
            s1 = cfma(L128[1], s1, b);
          }
        }
        sts128f(sb + A_TAB + (w * 32 + lane) * 16, s0.r, s0.i, s1.r, s1.i);
        mbar_arrive(sb + A_SB + 8 * w);
      }
      uint8_t* gh = (uint8_t*)g_H + (size_t)(tt * 20 + pg * 4 + w * 2) * SLOT;
      mbar_wait(sb + A_HS + 16 * w, 0);
      if (lane == 0) {
        bulk_s2g(gh, sb + 1 * SLOT + w * 8192, 8192);
        bulk_s2g(gh + 16384, sb + 4 * SLOT + w * 8192, 8192);
      }
      __syncwarp();
      mbar_wait(sb + A_HS + 16 * w + 8, 0);
      if (lane == 0) {
        bulk_s2g(gh + 8192, sb + 2 * SLOT + w * 8192, 8192);
        asm volatile("cp.async.bulk.commit_group;" ::: "memory");
        bulk_s2g(gh + 24576, sb + 5 * SLOT + w * 8192, 8192);
        asm volatile("cp.async.bulk.commit_group;" ::: "memory");
        asm volatile("cp.async.bulk.wait_group 1;" ::: "memory");
        asm volatile("st.relaxed.gpu.global.u32 [%0], %1;" ::"l"(fp), "r"(epoch) : "memory");
        if (w == 0) STAMP(22);
        asm volatile("cp.async.bulk.wait_group 0;" ::: "memory");
        asm volatile("st.relaxed.gpu.global.u32 [%0], %1;" ::"l"(fp + 1), "r"(epoch) : "memory");
        if (w == 0) STAMP(7);
        mbar_arrive(sb + A_HD);
      }
    }
  }
}

__device__ __forceinline__ void roleA_cons(const Params& P, uint32_t sb, int cta PROF_ARG) {
  const int tid = threadIdx.x, warp = __shfl_sync(0xffffffffu, tid >> 5, 0), lane = tid & 31;
  const int pg = cta >> 4, tt = cta & 15, rank = cta & 1;
  {
    cluster_arrive_relaxed();
    asm volatile("setmaxnreg.inc.sync.aligned.u32 208;");
    bar_sync(0, 384);
    if (tid == 0) STAMP(27);
    const int w = warp >> 2, wq = warp & 3, r = lane >> 2, q = lane & 3;
    const bool leader = (tid & 127) == 0;
    const uint32_t peer_ce = mapa(sb + A_CE, rank ^ 1);
    const uint32_t d0 = mkdesc(sb, 16), dw = d0 + w * 512;
    float are[64], aim[64];
#pragma unroll 1
    for (int kb = 0; kb < 10; kb++) {
      const int s = kb & 3;
      mbar_wait(sb + A_G1F + 8 * s, (kb >> 2) & 1);
      if (tid == 0 && kb == 0) STAMP(2);
      const uint32_t so = s * (3 * SLOT >> 4);
      wg_fence();
#pragma unroll
      for (int k = 0; k < 4; k++) {
        WSS<128, 0, 0, 1, 1>::run(are, dw + so + (SLOT >> 4) + 2 * k, d0 + so + 2 * k, (kb | k) != 0);
        WSS<128, 0, 0, 1, 1>::run(aim, dw + so + (2 * SLOT >> 4) + 2 * k, d0 + so + 2 * k, (kb | k) != 0);
      }
      wg_commit();
      if (kb == 0) cluster_wait();
      wg_wait<1>();
      if (leader) {
        if (kb > 0 && kb < 7) mbar_arrive(sb + A_G1E + 8 * ((kb - 1) & 3));
        if (kb == 7) {
#pragma unroll
          for (int i = 0; i < 3; i++) { mbar_arrive(sb + A_CE + 8 * i); mbar_arrive_cluster(peer_ce + 8 * i); }
        }
        if (kb == 8) { mbar_arrive(sb + A_CE + 24); mbar_arrive_cluster(peer_ce + 24); }
      }
    }
    mbar_wait(sb + A_EPB, 0);
    const uint32_t epoch = lds32(sb + A_EPV);
    cf lam[2], c2[2], L32[2];
#pragma unroll
    for (int z = 0; z < 2; z++) {
      const uint4 t = lds128(sb + A_TAB + (w * 64 + wq * 16 + r + 8 * z) * 16);
      lam[z].r = __uint_as_float(t.x); lam[z].i = __uint_as_float(t.y); c2[z].r = __uint_as_float(t.z); c2[z].i = __uint_as_float(t.w);
      cf L = lam[z];
#pragma unroll
      for (int i = 0; i < 5; i++) L = cmul(L, L);
      L32[z] = L;
      asm volatile("" : "+f"(L32[z].r), "+f"(L32[z].i));
    }
    wg_wait<0>();
    fence_regs<64>(are); fence_regs<64>(aim);
    mbar_arrive(sb + A_G1D);
    if (tid == 0) STAMP(3);

    cf e[2];
#pragma unroll
    for (int z = 0; z < 2; z++) { e[z].r = are[2 * z]; e[z].i = aim[2 * z]; }
#pragma unroll
    for (int u = 1; u < 32; u++) {
#pragma unroll
      for (int z = 0; z < 2; z++) {
        const int idx = 4 * (u >> 1) + 2 * z + (u & 1);
        cf b; b.r = are[idx]; b.i = aim[idx];
        e[z] = cfma(lam[z], e[z], b);
      }
    }
    const uint32_t tag_r = epoch & 15u, tag_i = (epoch >> 4) & 15u;
    cf init[2], Lq[2];
    unsigned long long* ep = &g_E[pg * 128 + w * 64 + wq * 16 + r];
#pragma unroll
    for (int z = 0; z < 2; z++) {
      cf v = cshfl_up(e[z], 1); if (q >= 1) e[z] = cfma(L32[z], v, e[z]);
      const cf L64 = cmul(L32[z], L32[z]);
      v = cshfl_up(e[z], 2); if (q >= 2) e[z] = cfma(L64, v, e[z]);
      if (q == 3 && tt < 15) {
        const uint32_t a = (__float_as_uint(e[z].r) & ~15u) | tag_r, b = (__float_as_uint(e[z].i) & ~15u) | tag_i;
        asm volatile("st.relaxed.gpu.global.u64 [%0], %1;" ::"l"(ep + tt * 640 + 8 * z), "l"(((unsigned long long)b << 32) | a) : "memory");
      }
      v = cshfl_up(e[z], 1); if (q == 0) { v.r = 0.f; v.i = 0.f; }
      init[z] = v;
      Lq[z].r = 1.f; Lq[z].i = 0.f;
      if (q & 1) Lq[z] = L32[z];
      if (q & 2) Lq[z] = cmul(Lq[z], L64);
    }
    if (tid == 0) STAMP(4);
    {
      mbar_wait(sb + A_SB + 8 * w, 0);
#pragma unroll
      for (int z = 0; z < 2; z++) {
        const float2 t = lds64f(sb + A_TAB + (w * 64 + wq * 16 + r + 8 * z) * 8);
        cf S; S.r = t.x; S.i = t.y;
        init[z] = cfma(Lq[z], S, init[z]);
      }
    }
    if (tid == 0) STAMP(5);
    const uint32_t mrow = wq * 16 + (lane & 7) + 8 * ((lane >> 3) & 1);
    const uint32_t sw = lane & 7, hi = lane >> 4;
    {
      const uint32_t rbase = sb + w * 8192 + mrow * 128;
#pragma unroll
      for (int jp = 0; jp < 8; jp++) {
        uint32_t pr[4], pi[4];
#pragma unroll
        for (int jj = 0; jj < 2; jj++) {
#pragma unroll
          for (int z = 0; z < 2; z++) {
            const int idx = 4 * (2 * jp + jj) + 2 * z;
            cf b0, b1; b0.r = are[idx]; b0.i = aim[idx]; b1.r = are[idx + 1]; b1.i = aim[idx + 1];
            const cf g0 = cfma(lam[z], init[z], b0);
            const cf g1 = cfma(lam[z], g0, b1);
            init[z] = g1;
            pr[2 * jj + z] = pack_bf16(fmaf(c2[z].r, g0.r, -c2[z].i * g0.i), fmaf(c2[z].r, g1.r, -c2[z].i * g1.i));
            pi[2 * jj + z] = pack_bf16(fmaf(-c2[z].r, g0.i, -c2[z].i * g0.r), fmaf(-c2[z].r, g1.i, -c2[z].i * g1.r));
          }
        }
        const uint32_t chunk = ((2 * jp) & 7) + hi;
        const uint32_t off = rbase + ((chunk ^ sw) << 4) + (jp >= 4 ? SLOT : 0);
        stsm4(off + 1 * SLOT, pr[0], pr[1], pr[2], pr[3]);
        stsm4(off + 4 * SLOT, pi[0], pi[1], pi[2], pi[3]);
        if ((jp & 3) == 3) { fence_async_smem(); mbar_arrive(sb + A_HS + 16 * w + 8 * (jp >> 2)); }
      }
    }
    if (tid == 0) STAMP(6);
    float acc[64];
    {
      mbar_wait(sb + A_XF, 0);
      const uint32_t xbase = sb + 12 * SLOT + (w * 64 + mrow) * 128;
#pragma unroll
      for (int jp = 0; jp < 8; jp++) {
        uint32_t xr[4];
        ldsm4(xbase + (jp >> 2) * SLOT + (((((2 * jp) & 7) + hi) ^ sw) << 4), xr);
#pragma unroll
        for (int jj = 0; jj < 2; jj++) {
          const uint32_t dk = lds32(sb + A_DSK + (4 * (2 * jp + jj) + q) * 4);
          const uint32_t a = bmul2(xr[2 * jj], dk), b = bmul2(xr[2 * jj + 1], dk);
          const int idx = 4 * (2 * jp + jj);
          acc[idx] = bf_lo(a); acc[idx + 1] = bf_hi(a); acc[idx + 2] = bf_lo(b); acc[idx + 3] = bf_hi(b);
        }
      }
    }
    fence_regs<64>(acc);
    if (tid == 0) STAMP(8);
#pragma unroll 1
    for (int ci = 0; ci < 20; ci++) {
      const int ring = ci & 3;
      uint32_t dA;
      if (ci < 4) { mbar_wait(sb + A_HS + 16 * (ci >> 1) + 8 * w, 0); dA = d0 + w * 1024 + (((1 + 3 * (ci & 1)) * SLOT) >> 4) + (ci >> 1) * 512; }
      else { mbar_wait(sb + A_HF + 8 * ring, ((ci >> 2) - 1) & 1); dA = dw + (hslot(ring) >> 4); }
      mbar_wait(sb + A_CF + 8 * ring, (ci >> 2) & 1);
      if (tid == 0 && (ci & 1) == 0) STAMP(12 + (ci >> 1));
      const uint32_t dB = d0 + (cslot(ring) >> 4);
      wg_fence();
#pragma unroll
      for (int k = 0; k < 4; k++) WSS<128, 1, 0, 1, 1>::run(acc, dA + k * 128, dB + 2 * k, 1);
      wg_commit();
      wg_wait<1>();
      if (leader) {
        if (ci > 0 && ci <= 16) { mbar_arrive(sb + A_CE + 8 * ((ci - 1) & 3)); mbar_arrive_cluster(peer_ce + 8 * ((ci - 1) & 3)); }
        if (ci > 4) mbar_arrive(sb + A_HE + 8 * ((ci - 1) & 3));
      }
    }
    wg_wait<0>();
    fence_regs<64>(acc);
    if (tid == 0) STAMP(9);
    {
      mbar_wait(sb + A_HD, 0);
      const uint32_t ob = sb + (1 + 3 * w) * SLOT + (wq * 16 + r) * 128 + (q & 1) * 8;
      const bool odd = r & 1;
#pragma unroll
      for (int bx = 0; bx < 4; bx++) {
#pragma unroll
        for (int jj = 0; jj < 4; jj++) {
          const int i0 = 4 * (4 * bx + jj), i1 = 4 * (4 * bx + (jj ^ 2));
          const uint32_t ch = (uint32_t)(((odd ? (jj ^ 2) : jj) * 2 + (q >> 1)) ^ r) << 4;
          sts64f(ob + bx * 8192 + ch, odd ? acc[i1] : acc[i0], odd ? acc[i1 + 1] : acc[i0 + 1]);
          sts64f(ob + bx * 8192 + 1024 + ch, odd ? acc[i1 + 2] : acc[i0 + 2], odd ? acc[i1 + 3] : acc[i0 + 3]);
        }
        if (bx & 1) {
          fence_async_smem();
          bar_sync(1 + w, 128);
          if (leader) {
            tma5d_store(&P.oa, sb + (1 + 3 * w) * SLOT + (bx - 1) * 8192, pg * 128 + 32 * (bx - 1), 8 * w, tt);
            tma5d_store(&P.oa, sb + (1 + 3 * w) * SLOT + bx * 8192, pg * 128 + 32 * bx, 8 * w, tt);
          }
        }
      }
      if (leader) {
        asm volatile("cp.async.bulk.commit_group;" ::: "memory");
        asm volatile("cp.async.bulk.wait_group.read 0;" ::: "memory");
      }
    }
    if (tid == 0) { STAMP(10); STAMPG(1); }
  }
}

constexpr uint32_t B_U = 0, B_STRIP = 132 * 16, B_CH = 265 * 16, B_USZ = 16 * B_CH;
__host__ __device__ constexpr uint32_t chbase(int c) { return (uint32_t)c * B_CH; }
constexpr uint32_t B_KC = B_USZ, KC_C1 = 1048 * 4, KC_BUF = 2096 * 4;
constexpr uint32_t B_X = B_KC + 4 * KC_BUF, X_Z = 136 * 16, X_CLS = 2 * X_Z, X_BUF = 4 * X_CLS;
constexpr uint32_t B_OST = B_X + 2 * X_BUF;
constexpr uint32_t B_Q1 = B_OST + 16384, B_Q0 = B_Q1 + 32768;
constexpr uint32_t ST_K = 33 * 512, ST_CH = ST_K + 32 * 512, B_ST = (B_KC + 2 * KC_BUF + 511) / 512 * 512;
constexpr uint32_t B_BAR = B_ST + 4 * ST_CH;
constexpr uint32_t B_KST = B_BAR  , B_KSE = B_BAR + 64  , B_KF = B_BAR + 96, B_KE = B_BAR + 128, B_KR = B_BAR + 160, B_PF = B_BAR + 192,
                   B_QF = B_BAR + 200  , B_GD = B_BAR + 216, B_ZR = B_BAR + 224  , B_SHK = B_BAR + 240  , B_SSD = B_BAR + 496  ;
static_assert(B_X % 128 == 0 && B_OST % 128 == 0, "align");
static_assert(B_Q0 + 32768 <= B_BAR && B_BAR + 576 <= SMEM_BYTES, "smem");

struct BGeom {
  int W0;
  bool wide;
  int t;
  int nside, octO, octS, jq;
  uint32_t order;
  __device__ __forceinline__ BGeom(int cta) {
    const int g = cta / 10, idx = cta - 10 * g;
    t = (int)((0x1032443210ull >> (4 * idx)) & 15);
    W0 = 128 * g + (idx >= 5 ? 64 : 0) + (int)((0x32110u >> (4 * t)) & 15) * 16;
    nside = t < 2 ? 6 : 4;
    octO = (0x11200u >> (4 * t)) & 15; octS = (0x02111u >> (4 * t)) & 15;
    jq = (t == 2 || t == 4) ? 4 : 0;
    wide = (t == 2 || t == 3);
    order = t == 0 ? 0x543210u : t == 1 ? 0x325410u : jq ? 0x7654u : 0x3210u;
  }
  __device__ __forceinline__ int slot(int i) const { return i < nside ? (int)((order >> (4 * i)) & 15u) : 8 + i - nside; }
  __device__ __forceinline__ int wch(int sl) const {
    if (sl >= 8) return 8 * octO + sl - 8;
    if (t == 1 && sl >= 4) return sl - 6;
    return 8 * octS + sl;
  }
};

__host__ __device__ constexpr int conv_order(int s) { return (s & 1) ? 15 - (s >> 1) : (s >> 1); }
template <int S> __device__ __forceinline__ void conv_lds(uint32_t* f, uint32_t kaddr) {
  const uint32_t a = kaddr + 256 * conv_order(S);
  f[8 * S + 1] = lds32(a); f[8 * S + 0] = lds32(a + 16); f[8 * S + 2] = lds32(a + 32); f[8 * S + 4] = lds32(a + 48); f[8 * S + 6] = lds32(a + 64);
}
template <int S> __device__ __forceinline__ void conv_dup(uint32_t* f, uint32_t zero) {
  asm volatile("xor.b32 %0, %1, %2;" : "=r"(f[8 * S + 3]) : "r"(f[8 * S + 0]), "r"(zero));
  asm volatile("xor.b32 %0, %1, %2;" : "=r"(f[8 * S + 5]) : "r"(f[8 * S + 2]), "r"(zero));
  asm volatile("xor.b32 %0, %1, %2;" : "=r"(f[8 * S + 7]) : "r"(f[8 * S + 4]), "r"(zero));
}
template <int S> __device__ __forceinline__ void conv_mma(float* acc, const uint32_t* f, uint64_t ud) {
  constexpr int M = conv_order(S);
  WRS<128 - 8 * M>::run(acc, f[8 * S], f[8 * S + 1], f[8 * S + 2], f[8 * S + 3], ud + 8 * M, M != 0);
  WRS<128 - 8 * M>::run(acc, f[8 * S + 4], f[8 * S + 5], f[8 * S + 6], f[8 * S + 7], ud + 8 * M + 1, 1);
}
template <int S0, int S1> struct ConvRange {
  static __device__ __forceinline__ void lds(uint32_t* f, uint32_t ka) { conv_lds<S0>(f, ka); ConvRange<S0 + 1, S1>::lds(f, ka); }
  static __device__ __forceinline__ void dup(uint32_t* f, uint32_t z) { conv_dup<S0>(f, z); ConvRange<S0 + 1, S1>::dup(f, z); }
  static __device__ __forceinline__ void mma(float* acc, const uint32_t* f, uint64_t ud) { conv_mma<S0>(acc, f, ud); ConvRange<S0 + 1, S1>::mma(acc, f, ud); }
};
template <int S1> struct ConvRange<S1, S1> {
  static __device__ __forceinline__ void lds(uint32_t*, uint32_t) {}
  static __device__ __forceinline__ void dup(uint32_t*, uint32_t) {}
  static __device__ __forceinline__ void mma(float*, const uint32_t*, uint64_t) {}
};
template <int J> __device__ __forceinline__ void dump_step(const float* acc, uint32_t xw) {
  stsm4t(xw + J * 256, pack_bf16(acc[8 * J], acc[8 * J + 1]), pack_bf16(acc[8 * J + 2], acc[8 * J + 3]),
         pack_bf16(acc[8 * J + 4], acc[8 * J + 5]), pack_bf16(acc[8 * J + 6], acc[8 * J + 7]));
}

__device__ __forceinline__ void final_tile(uint32_t za, uint32_t qa, uint32_t st, int tb, uint32_t pitch8, bool on) {
  uint32_t z[4], qq[4];
  ldsm4t(za - tb * 32, z);
  ldsm4(qa + tb * 512, qq);
#pragma unroll
  for (int m = 0; m < 4; m++) {
    const uint32_t o = bmul2(qq[m], z[m]);
    if (on) sts64f(st + m * pitch8, bf_lo(o), bf_hi(o));
  }
}
__device__ __forceinline__ void tma2d_store(const CUtensorMap* m, uint32_t src, int c0, int c1) {
  asm volatile("cp.async.bulk.tensor.2d.global.shared::cta.bulk_group [%0, {%2, %3}], [%1];" ::"l"(m), "r"(src), "r"(c0), "r"(c1) : "memory");
}
__device__ __forceinline__ void final_last(const Params& P, uint32_t sb, int col, int warp, int lane) {
  const int mi = lane >> 3, mr = lane & 7, i = lane >> 2, q = lane & 3;
  const uint32_t za = sb + B_U + chbase(8 + mr) + (1 - (mi & 1)) * B_STRIP + (127 - (mi >> 1)) * 16;
  const uint32_t qa = sb + B_Q0 + (8 * mi + 7 - mr) * 16;
  const uint32_t st = sb + B_X + (7 - i) * 32 + q * 8;
#pragma unroll 1
  for (int ck = warp >> 2; ck < 8; ck += 3) {
    const int tb = ck * 8 + (warp & 3) * 2;
    final_tile(za, qa, st + tb * 1024, tb, 256, true);
    final_tile(za, qa, st + tb * 1024 + 1024, tb + 1, 256, true);
    fence_async_smem();
    bar_sync(6 + (warp >> 2), 128);
    if ((warp & 3) == 0 && lane == 0) tma2d_store(&P.ob, sb + B_X + ck * 8192, col, ck * 256);
  }
  if ((warp & 3) == 0 && lane == 0) {
    asm volatile("cp.async.bulk.commit_group;" ::: "memory");
    asm volatile("cp.async.bulk.wait_group.read 0;" ::: "memory");
  }
}
__device__ __forceinline__ void b_issue_chunk(const Params& P, uint32_t sb, int c, int W0, bool wide) {
  const uint32_t dst = sb + B_ST + (wide ? (c & 3) * ST_CH : c * (ST_CH / 2)), bar = sb + B_KST + 8 * c;
  mbar_expect(bar, wide ? ST_CH : ST_CH / 2);
  tma3d(dst, wide ? &P.k : &P.k16, W0, c * 32 - 1, 0, bar);
  tma3d(dst + (wide ? ST_K : ST_K / 2), wide ? &P.v : &P.v16, W0, c * 32, 0, bar);
}
__device__ __forceinline__ void b_issue_filter(const Params& P, uint32_t sb, int i, int gch) {
  mbar_expect(sb + B_KR + 8 * (i & 3), 4096);
  bulk_g2s(sb + B_KC + (i & 3) * KC_BUF + 32, P.ssmk + (size_t)gch * SEQ, 4096, sb + B_KR + 8 * (i & 3));
}

__device__ __forceinline__ void b_entry(const Params& P, uint32_t sb, int cta PROF_ARG) {
  const BGeom G(cta);
  b_issue_chunk(P, sb, 0, G.W0, G.wide);
  STAMP(26);
  const int nw = G.wide ? 32 : 16, pre = G.t == 1 ? 8 : 0;
  mbar_expect(sb + B_PF, nw * 10 + pre * 2);
  bulk_g2s(sb + B_SHK, P.shk + G.W0 * 4, nw * 8, sb + B_PF);
  bulk_g2s(sb + B_SSD + 16 - pre * 2, P.ssmd + G.W0 - pre, (nw + pre) * 2, sb + B_PF);
#pragma unroll 1
  for (int i = 1; i < (G.wide ? 4 : 8); i++) {
    b_issue_chunk(P, sb, i, G.W0, G.wide);
    if (i < 3) b_issue_filter(P, sb, i - 1, G.W0 + G.wch(G.slot(i - 1)));
  }
}

__device__ __forceinline__ void roleB_serv(const Params& P, uint32_t sb, int cta PROF_ARG) {
  const int tid = threadIdx.x, warp = __shfl_sync(0xffffffffu, tid >> 5, 0), lane = tid & 31;
  asm volatile("setmaxnreg.dec.sync.aligned.u32 56;");
  const BGeom G(cta);
  const int nch = G.nside + 8;
  if (warp == 8) {
    cluster_arrive_relaxed();
    bar_sync(9, 128);
    if (G.wide) {
#pragma unroll 1
      for (int i = 4; i < 8; i++) {
        mbar_wait(sb + B_KSE + 8 * (i - 4), 0);
        if (lane == 0) b_issue_chunk(P, sb, i, G.W0, true);
        __syncwarp();
      }
    }
    if (lane >= 2 && lane < nch)
      asm volatile("cp.async.bulk.prefetch.L2.global [%0], %1;" ::"l"(P.ssmk + (size_t)(G.W0 + G.wch(G.slot(lane))) * SEQ), "r"(4096) : "memory");
    if (lane == 0) { prefetch_tmap(&P.q); prefetch_tmap(&P.ob); prefetch_tmap(G.t ? &P.o4 : &P.oh); STAMP(27); }
    __syncwarp();
    cluster_wait();
    bar_sync(3, 384);
    if (lane == 0) {
      if (G.t == 0) {
        const uint32_t dst = mapa(sb + B_U + chbase(4), 1), bar = mapa(sb + B_ZR, 1);
        asm volatile("cp.async.bulk.shared::cluster.shared::cta.mbarrier::complete_tx::bytes [%0], [%1], %2, [%3];" ::"r"(dst),
                     "r"(sb + B_U + chbase(6)), "r"(2 * B_CH - 16), "r"(bar) : "memory");
      }
      b_issue_filter(P, sb, 2, G.W0 + G.wch(G.slot(2))); b_issue_filter(P, sb, 3, G.W0 + G.wch(G.slot(3)));
    }
#pragma unroll 1
    for (int i = 4; i < 12 || i < nch; i++) {
      if (i < nch) mbar_wait(sb + B_KE + 8 * (i & 3), ((i >> 2) - 1) & 1);
      if (lane == 0) {
        if (i < nch) b_issue_filter(P, sb, i, G.W0 + G.wch(G.slot(i)));
        if (i < 12) {
          const int r0 = (i & 3) * 512;
          const uint32_t dst = sb + (i < 8 ? B_Q1 : B_Q0) + r0 * 16, bar = sb + B_QF + (i < 8 ? 8 : 0);
          const int col = G.W0 + 8 * (i < 8 ? G.octS : G.octO);
          tma2d(dst, &P.q, col, r0, bar);
          tma2d(dst + 4096, &P.q, col, r0 + 256, bar);
        }
      }
      __syncwarp();
    }
  } else if (warp == 9) {
    if (lane < 8) {
      const int b = lane >> 2, part = lane & 3;
      sts128(sb + B_KC + b * KC_BUF + (part >> 1) * KC_C1 + (part & 1) * 16, 0, 0, 0, 0);
    }
    __syncwarp();
    cluster_arrive_relaxed();
    bar_sync(0, 384);
    bar_sync(9, 128);
#pragma unroll 1
    for (int i = 0; i < nch; i++) {
      const int kb = i & 3;
      const uint32_t src = sb + B_KC + kb * KC_BUF + 32;
      mbar_wait(sb + B_KR + 8 * kb, (i >> 2) & 1);
#pragma unroll
      for (int h = 0; h < 8; h++) {
        const int x = lane + 32 * h;
        const uint4 kk = lds128(src + x * 16);
        const uint32_t nx = (x < 255) ? lds32(src + x * 16 + 16) : 0u;
        sts128(src + KC_C1 + x * 16, __byte_perm(kk.x, kk.y, 0x5432), __byte_perm(kk.y, kk.z, 0x5432), __byte_perm(kk.z, kk.w, 0x5432),
               __byte_perm(kk.w, nx, 0x5432));
        if (x == 0) sts32(src + KC_C1 - 4, kk.x << 16);
      }
      mbar_arrive(sb + B_KF + 8 * kb);
      if (i == 1) {
        cluster_wait();
        bar_sync(3, 384);
        if (lane < 8) {
          const int b = 2 + (lane >> 2), part = lane & 3;
          sts128(sb + B_KC + b * KC_BUF + (part >> 1) * KC_C1 + (part & 1) * 16, 0, 0, 0, 0);
        }
        __syncwarp();
      }
    }
  } else {
    if (warp == 10) {
      if (lane == 0) {
        for (int i = 0; i < 4; i++) { mbar_init(sb + B_KSE + 8 * i, 2); mbar_init(sb + B_KF + 8 * i, 32); mbar_init(sb + B_KE + 8 * i, 4); }
        mbar_init(sb + B_QF, 1); mbar_init(sb + B_QF + 8, 1); mbar_init(sb + B_GD, 4 * G.nside); mbar_init(sb + B_ZR, 1);
        asm volatile("fence.mbarrier_init.release.cluster;" ::: "memory");
        mbar_expect(sb + B_QF, 32768); mbar_expect(sb + B_QF + 8, 32768);
        mbar_expect(sb + B_ZR, G.t == 0 ? 2 * 264 * 16 : 2 * B_CH - 16);
      }
    } else {
      sts128(sb + B_U + chbase(lane >> 1) + (lane & 1) * B_STRIP + 128 * 16, 0, 0, 0, 0);
      fence_async_smem();
    }
    __syncwarp();
    cluster_arrive_relaxed();
    bar_sync(0, 384);
    bar_sync(9, 128);
    cluster_wait();
    bar_sync(3, 384);
    const int mi = lane >> 3, mr = lane & 7, q = lane & 3;
    const uint32_t za = sb + B_U + chbase(mr) + (1 - (mi & 1)) * B_STRIP + (127 - (mi >> 1)) * 16;
    const uint32_t qa = sb + B_Q1 + (8 * mi + 7 - mr) * 16;
    const bool st = G.t != 0;
    const uint32_t so = st ? (7 - (lane >> 2)) * 16 + (q & 1) * 8 : (7 - (lane >> 2)) * 32 + q * 8;
    const bool on = !st || ((q >> 1) == (G.jq >> 2));
    mbar_wait(sb + B_GD, 0); mbar_wait(sb + B_QF + 8, 0);
    if (G.t == 0) mbar_wait(sb + B_ZR, 0);
    if (tid == 320) STAMP(24);
#pragma unroll 1
    for (int ck = warp - 10; ck < 16; ck += 2) {
      const uint32_t ost = sb + B_OST + (ck & 3) * 4096;
      if (lane == 0) asm volatile("cp.async.bulk.wait_group.read 1;" ::: "memory");
      __syncwarp();
#pragma unroll
      for (int u = 0; u < 4; u++) final_tile(za, qa, ost + so + (st ? u * 512 : u * 1024), ck * 4 + u, st ? 128 : 256, on);
      fence_async_smem();
      __syncwarp();
      if (lane == 0) {
        tma2d_store(st ? &P.o4 : &P.oh, ost, DM + G.W0 + 8 * G.octS + G.jq, ck * 128);
        asm volatile("cp.async.bulk.commit_group;" ::: "memory");
      }
    }
    if (lane == 0) asm volatile("cp.async.bulk.wait_group.read 0;" ::: "memory");
    __syncwarp();
    if (tid == 320) STAMP(25);
  }
  bar_sync(0, 384);
  mbar_wait(sb + B_QF, 0);
  final_last(P, sb, DM + G.W0 + 8 * G.octO, warp, lane);
}

__device__ __forceinline__ void roleB_conv(const Params& P, uint32_t sb, int cta PROF_ARG) {
  const int tid = threadIdx.x, warp = __shfl_sync(0xffffffffu, tid >> 5, 0), lane = tid & 31, wg = warp >> 2, t128 = tid & 127;
  const BGeom G(cta);
  const int nit = (G.nside + 8) >> 1;
  cluster_arrive_relaxed();
  bar_sync(0, 384);
  {
    const uint32_t pitch = G.wide ? 64 : 32, swm = G.wide ? 0x30 : 0x10;
    mbar_wait(sb + B_PF, 0);
#pragma unroll 1
    for (int task = warp; task < 16; task += 8) {
      const int c = task >> 1, o = (task & 1) + (G.wide ? 1 : 0);
      int dl = 0, jlo = G.jq, jhi = G.jq + 4;
      if (o == G.octO) { dl = 8; jlo = 0; jhi = 8; }
      else if (G.t == 0) jhi = 8;
      uint32_t wt[4][4];
#pragma unroll
      for (int cp = 0; cp < 4; cp++) {
        const uint4 ww = lds128(sb + B_SHK + o * 64 + cp * 16);
        wt[0][cp] = __byte_perm(ww.x, ww.z, 0x5410); wt[1][cp] = __byte_perm(ww.x, ww.z, 0x7632);
        wt[2][cp] = __byte_perm(ww.y, ww.w, 0x5410); wt[3][cp] = __byte_perm(ww.y, ww.w, 0x7632);
      }
      mbar_wait(sb + B_KST + 8 * c, 0);
      if (tid == 0) STAMP(task < 8 ? 2 : 3);
      uint32_t kr[11][4];
      const uint32_t ka = sb + B_ST + (G.wide ? (c & 3) * ST_CH : c * (ST_CH / 2)) + lane * pitch + o * 16;
#pragma unroll
      for (int i = 0; i < 11; i++) {
        const uint32_t a = ka + (i < 3 ? (5 + i) * 33 : 1 + (i - 3) * 33) * pitch;
        const uint4 t = lds128(a ^ ((a >> 3) & swm));
        kr[i][0] = t.x; kr[i][1] = t.y; kr[i][2] = t.z; kr[i][3] = t.w;
      }
      uint32_t kv[8][4];
#pragma unroll
      for (int i = 0; i < 8; i++) {
        const uint4 vt = lds128((ka ^ ((ka >> 3) & swm)) + (264 + i * 32) * pitch);
        const uint32_t vr[4] = {vt.x, vt.y, vt.z, vt.w};
#pragma unroll
        for (int cp = 0; cp < 4; cp++) {
          uint32_t a = bmul2(kr[i][cp], wt[3][cp]);
          a = badd2(a, bmul2(kr[i + 1][cp], wt[2][cp]));
          a = badd2(a, bmul2(kr[i + 2][cp], wt[1][cp]));
          a = badd2(a, bmul2(kr[i + 3][cp], wt[0][cp]));
          kv[i][cp] = bmul2(a, vr[cp]);
        }
      }
      __syncwarp();
      if (c < 4 && lane == 0) mbar_arrive(sb + B_KSE + 8 * c);
      const int kap = c * 32 + lane;
      const uint32_t ua = sb + B_U + dl * (int)B_CH + (1 - (kap & 1)) * B_STRIP + (127 - (kap >> 1)) * 16;
#pragma unroll
      for (int j = 0; j < 8; j++) {
        const uint32_t sel = (j & 1) ? 0x7632 : 0x5410;
        if (j >= jlo && j < jhi)
          sts128(ua + j * B_CH, __byte_perm(kv[7][j >> 1], kv[6][j >> 1], sel), __byte_perm(kv[5][j >> 1], kv[4][j >> 1], sel),
                 __byte_perm(kv[3][j >> 1], kv[2][j >> 1], sel), __byte_perm(kv[1][j >> 1], kv[0][j >> 1], sel));
      }
    }
    fence_async_smem();
    if (tid == 0) STAMP(4);
  }
  asm volatile("setmaxnreg.inc.sync.aligned.u32 224;");
  const int wq = warp & 3, i = lane >> 2, q = lane & 3;
  const uint32_t xb = sb + B_X + wg * X_BUF;
  const uint32_t koff = ((i & 1) ? KC_C1 : 0) + (16 * wq + 4 + q - ((i + 1) >> 1)) * 4;
  const uint32_t xw = xb + wq * X_CLS + ((lane >> 3) & 1) * X_Z + (8 * (lane >> 4) + (lane & 7) + 6 - 2 * wq) * 16;
  const int zo = wq >> 1, jo = 8 * (wq & 1);
  const uint32_t xr = xb + zo * X_Z + (8 * jo + lane + 6) * 16;
  const uint32_t uo = zo * B_STRIP + (8 * jo + lane) * 16;
  if (wg == 1) bar_arrive(4, 256);
  uint32_t f[128];
  mbar_wait(sb + B_KF + 8 * wg, 0);
  ConvRange<0, 16>::lds(f, sb + B_KC + wg * KC_BUF + koff);
  ConvRange<0, 16>::dup(f, P.zero);
  __syncwarp();
  if (lane == 0) mbar_arrive(sb + B_KE + 8 * wg);
  cluster_wait();
  if (tid == 0) STAMP(30);
  bar_sync(3, 384);
  if (t128 < 48) {
    const int cls = t128 >> 4, z = (t128 >> 3) & 1, k = t128 & 7;
    if (k < 2 * (cls + 1)) sts128(xb + (cls + 1) * X_CLS + z * X_Z + (133 - k) * 16, 0, 0, 0, 0);
  }
#pragma unroll 1
  for (int it = 0; it < nit; it++) {
    const int pos = 2 * it + wg, sl = G.slot(pos);
    const uint32_t ub = sb + B_U + chbase(sl);
    float acc[64];
    {
      const uint64_t ud = (uint64_t)mkdesc(ub, B_STRIP) | (8ull << 32);
      if (it == 1 && G.t == 1) mbar_wait(sb + B_ZR, 0);
      bar_sync(4 + wg, 256);
      if (tid == 0) STAMP(5 + 2 * it);
      wg_fence();
      ConvRange<0, 8>::mma(acc, f, ud);
      wg_commit();
      ConvRange<8, 14>::mma(acc, f, ud);
      if (pos + 1 < 2 * nit) bar_arrive(5 - wg, 256);
      ConvRange<14, 16>::mma(acc, f, ud);
      wg_commit();
    }
    const int kb = (pos + 2) & 3;
    if (it + 1 < nit) mbar_wait(sb + B_KF + 8 * kb, ((pos + 2) >> 2) & 1);
    const uint32_t ka = sb + B_KC + kb * KC_BUF + koff;
    wg_wait<1>();
    ConvRange<0, 8>::lds(f, ka);
    ConvRange<0, 6>::dup(f, P.zero);
    wg_wait<0>();
    fence_regs<64>(acc);
    if (tid == 0) STAMP(6 + 2 * it);
    dump_step<0>(acc, xw); dump_step<1>(acc, xw); conv_lds<8>(f, ka); dump_step<2>(acc, xw); dump_step<3>(acc, xw); conv_lds<9>(f, ka);
    dump_step<4>(acc, xw); dump_step<5>(acc, xw); conv_lds<10>(f, ka); dump_step<6>(acc, xw); dump_step<7>(acc, xw); conv_lds<11>(f, ka);
    bar_sync(1 + wg, 128);
    const int wc = G.wch(sl);
    const uint32_t d2 = __byte_perm(lds32(sb + B_SSD + 16 + (wc >> 1) * 4), 0, (wc & 1) ? 0x3232 : 0x1010);
    uint32_t zz[8];
#pragma unroll
    for (int h = 0; h < 2; h++) {
      uint32_t kvr[4], p0[4], p1[4], p2[4], p3[4];
      ldsm4t(xr + h * 512, p0); ldsm4t(xr + X_CLS + h * 512, p1); ldsm4t(xr + 2 * X_CLS + h * 512, p2); ldsm4t(xr + 3 * X_CLS + h * 512, p3);
      ldsm4t(ub + uo + h * 512, kvr);
      if (h == 0) ConvRange<12, 14>::lds(f, ka); else ConvRange<14, 16>::lds(f, ka);
#pragma unroll
      for (int j = 0; j < 4; j++) {
        const uint32_t y = pack_bf16((bf_lo(p0[j]) + bf_lo(p1[j])) + (bf_lo(p2[j]) + bf_lo(p3[j])),
                                     (bf_hi(p0[j]) + bf_hi(p1[j])) + (bf_hi(p2[j]) + bf_hi(p3[j])));
        zz[4 * h + j] = badd2(y, bmul2(kvr[j], d2));
      }
    }
    stsm4t(ub + uo, zz[0], zz[1], zz[2], zz[3]);
    stsm4t(ub + uo + 512, zz[4], zz[5], zz[6], zz[7]);
    ConvRange<6, 16>::dup(f, P.zero);
    if (it == 1 && G.t == 1) {
      fence_async_smem();
      bar_sync(1 + wg, 128);
      if (t128 == 0) {
        const uint32_t dst = mapa(sb + B_U + chbase(sl + 2), 0), bar = mapa(sb + B_ZR, 0);
        asm volatile("cp.async.bulk.shared::cluster.shared::cta.mbarrier::complete_tx::bytes [%0], [%1], %2, [%3];" ::"r"(dst), "r"(ub),
                     "r"(264 * 16), "r"(bar) : "memory");
      }
    }
    __syncwarp();
    if (lane == 0) { if (it + 1 < nit) mbar_arrive(sb + B_KE + 8 * kb); if (pos < G.nside) mbar_arrive(sb + B_GD); }
  }
  if (tid == 0) STAMP(21);
  bar_sync(0, 384);
  mbar_wait(sb + B_QF, 0);
  if (tid == 0) STAMP(22);
  final_last(P, sb, DM + G.W0 + 8 * G.octO, warp, lane);
  if (tid == 0) { STAMP(23); STAMPG(1); }
}

__global__ void __cluster_dims__(2, 1, 1) __launch_bounds__(384, 1) fused_kernel(const __grid_constant__ Params P) {
  extern __shared__ __align__(1024) uint8_t smem[];
  uint32_t sb = smem_u32(smem);
  asm volatile("mov.b32 %0, %0;" : "+r"(sb));
  sb = __shfl_sync(0xffffffffu, sb, 0);
  if (sb & 1023u) asm volatile("trap;");
  const int b = blockIdx.x;
  if ((threadIdx.x >> 5) == 8) {
    if (threadIdx.x == 256) {
      const uint32_t fb = sb + (b < NA ? A_G1F : B_KST);
      for (int i = 0; i < 4; i++) mbar_init(fb + 8 * i, 1);
      if (b >= NA) {
        for (int i = 4; i < 8; i++) mbar_init(fb + 8 * i, 1);
        for (int i = 0; i < 5; i++) mbar_init(sb + B_KR + 8 * i, 1);
      }
      asm volatile("fence.mbarrier_init.release.cluster;" ::: "memory");
    }
    __syncwarp();
    bar_arrive(0, 384);
    if (threadIdx.x == 256) {
      if (b < NA) {
        a_issue_stage(P, sb, 0, b >> 4, b & 15); STAMP(25); a_issue_stage(P, sb, 1, b >> 4, b & 15);
      } else {
        b_entry(P, sb, b - NA PROF_PASS);
      }
    }
    __syncwarp();
  }
  if (b < 128 && threadIdx.x < 64) {
    const int l = threadIdx.x & 31;
    if (threadIdx.x < 32) {
      asm volatile("prefetch.global.L2 [%0];" ::"l"((const uint8_t*)P.xp + (size_t)(b * 16 + (l >> 1)) * 1280 + (l & 1) * 128));
    } else {
      if (l < 20) asm volatile("prefetch.global.L2 [%0];" ::"l"((const uint8_t*)(l < 10 ? P.brep : P.bimp) + (size_t)(b * 5 + (l % 10 >> 1)) * 1280 + (l & 1) * 128));
    }
  }
  if (threadIdx.x == 96) {
    if (b < NA) { prefetch_tmap(&P.x); prefetch_tmap(&P.bre); prefetch_tmap(&P.bim); }
    else { prefetch_tmap(&P.k16); prefetch_tmap(&P.v16); prefetch_tmap(&P.k); prefetch_tmap(&P.v); }
  }
  if (__builtin_expect(threadIdx.x >= 256, 1)) {
    if (b < NA) {
      roleA_prod(P, sb, b PROF_PASS);
    } else {
      roleB_serv(P, sb, b - NA PROF_PASS);
    }
  } else {
    if (b < NA) {
      roleA_cons(P, sb, b PROF_PASS);
    } else {
      roleB_conv(P, sb, b - NA PROF_PASS);
    }
  }
}

typedef CUresult (*EncFn)(CUtensorMap*, CUtensorMapDataType, cuuint32_t, void*, const cuuint64_t*, const cuuint64_t*, const cuuint32_t*,
                          const cuuint32_t*, CUtensorMapInterleave, CUtensorMapSwizzle, CUtensorMapL2promotion, CUtensorMapFloatOOBfill);

static void enc(EncFn fn, CUtensorMap* m, const void* base, int rank, const cuuint64_t* dims, const cuuint64_t* str, const cuuint32_t* box,
                CUtensorMapSwizzle sw, CUtensorMapL2promotion promo) {
  cuuint32_t es[5] = {1, 1, 1, 1, 1};
  fn(m, CU_TENSOR_MAP_DATA_TYPE_BFLOAT16, rank, (void*)base, dims, str, box, es, CU_TENSOR_MAP_INTERLEAVE_NONE, sw, promo,
     CU_TENSOR_MAP_FLOAT_OOB_FILL_NONE);
}

extern "C" void kernel_launch(void* const* d_in, const int* in_sizes, int n_in, void* d_out, int out_size) {
  static EncFn fn = nullptr;
  if (!fn) {
    void* f = nullptr; cudaDriverEntryPointQueryResult qr;
    cudaGetDriverEntryPoint("cuTensorMapEncodeTiled", &f, cudaEnableDefault, &qr);
    fn = (EncFn)f;
    cudaFuncSetAttribute(fused_kernel, cudaFuncAttributeMaxDynamicSharedMemorySize, SMEM_BYTES);
  }
  Params P;
  {
    const cuuint64_t dims[5] = {640, 2, 4, 16, 16}, str[4] = {1280, 32 * 1280, 2 * 1280, 128 * 1280};
    const cuuint32_t box[5] = {64, 2, 4, 16, 1};
    enc(fn, &P.x, d_in[0], 5, dims, str, box, CU_TENSOR_MAP_SWIZZLE_128B, CU_TENSOR_MAP_L2_PROMOTION_L2_128B);
  }
  {
    const cuuint64_t dims[2] = {640, 640}, str[1] = {1280};
    const cuuint32_t box[2] = {64, 128};
    enc(fn, &P.bre, d_in[3], 2, dims, str, box, CU_TENSOR_MAP_SWIZZLE_128B, CU_TENSOR_MAP_L2_PROMOTION_L2_128B);
    enc(fn, &P.bim, d_in[4], 2, dims, str, box, CU_TENSOR_MAP_SWIZZLE_128B, CU_TENSOR_MAP_L2_PROMOTION_L2_128B);
    const cuuint32_t boxh[2] = {64, 64};
    enc(fn, &P.cre, d_in[5], 2, dims, str, boxh, CU_TENSOR_MAP_SWIZZLE_128B, CU_TENSOR_MAP_L2_PROMOTION_L2_128B);
    enc(fn, &P.cim, d_in[6], 2, dims, str, boxh, CU_TENSOR_MAP_SWIZZLE_128B, CU_TENSOR_MAP_L2_PROMOTION_L2_128B);
  }
  {
    const cuuint64_t dims[3] = {640, 256, 8}, str[2] = {8 * 1280, 1280};
    const cuuint32_t box[3] = {32, 32, 8}, boxk[3] = {32, 33, 8};
    enc(fn, &P.k, d_in[10], 3, dims, str, boxk, CU_TENSOR_MAP_SWIZZLE_64B, CU_TENSOR_MAP_L2_PROMOTION_L2_128B);
    enc(fn, &P.v, d_in[11], 3, dims, str, box, CU_TENSOR_MAP_SWIZZLE_64B, CU_TENSOR_MAP_L2_PROMOTION_L2_128B);
    const cuuint32_t box16[3] = {16, 32, 8}, boxk16[3] = {16, 33, 8};
    enc(fn, &P.k16, d_in[10], 3, dims, str, boxk16, CU_TENSOR_MAP_SWIZZLE_32B, CU_TENSOR_MAP_L2_PROMOTION_L2_128B);
    enc(fn, &P.v16, d_in[11], 3, dims, str, box16, CU_TENSOR_MAP_SWIZZLE_32B, CU_TENSOR_MAP_L2_PROMOTION_L2_128B);
  }
  {
    const cuuint64_t dims[2] = {640, 2048}, str[1] = {1280};
    const cuuint32_t box[2] = {8, 256};
    enc(fn, &P.q, d_in[9], 2, dims, str, box, CU_TENSOR_MAP_SWIZZLE_NONE, CU_TENSOR_MAP_L2_PROMOTION_L2_128B);
  }
  {
    const cuuint64_t dims[5] = {1280, 2, 4, 16, 16}, str[4] = {5120, 32 * 5120, 2 * 5120, 128 * 5120};
    const cuuint32_t box[5] = {32, 2, 4, 8, 1}, es[5] = {1, 1, 1, 1, 1};
    fn(&P.oa, CU_TENSOR_MAP_DATA_TYPE_FLOAT32, 5, d_out, dims, str, box, es, CU_TENSOR_MAP_INTERLEAVE_NONE, CU_TENSOR_MAP_SWIZZLE_128B,
       CU_TENSOR_MAP_L2_PROMOTION_NONE, CU_TENSOR_MAP_FLOAT_OOB_FILL_NONE);
  }
  {
    const cuuint64_t dims[2] = {1280, 2048}, str[1] = {5120};
    const cuuint32_t box[2] = {8, 256}, boxh[2] = {8, 128}, box4[2] = {4, 128}, es[2] = {1, 1};
    fn(&P.o4, CU_TENSOR_MAP_DATA_TYPE_FLOAT32, 2, d_out, dims, str, box4, es, CU_TENSOR_MAP_INTERLEAVE_NONE, CU_TENSOR_MAP_SWIZZLE_NONE,
       CU_TENSOR_MAP_L2_PROMOTION_NONE, CU_TENSOR_MAP_FLOAT_OOB_FILL_NONE);
    fn(&P.ob, CU_TENSOR_MAP_DATA_TYPE_FLOAT32, 2, d_out, dims, str, box, es, CU_TENSOR_MAP_INTERLEAVE_NONE, CU_TENSOR_MAP_SWIZZLE_NONE,
       CU_TENSOR_MAP_L2_PROMOTION_NONE, CU_TENSOR_MAP_FLOAT_OOB_FILL_NONE);
    fn(&P.oh, CU_TENSOR_MAP_DATA_TYPE_FLOAT32, 2, d_out, dims, str, boxh, es, CU_TENSOR_MAP_INTERLEAVE_NONE, CU_TENSOR_MAP_SWIZZLE_NONE,
       CU_TENSOR_MAP_L2_PROMOTION_NONE, CU_TENSOR_MAP_FLOAT_OOB_FILL_NONE);
  }
  P.xp = (const __nv_bfloat16*)d_in[0];
  P.lre = (const __nv_bfloat16*)d_in[1];
  P.lim = (const __nv_bfloat16*)d_in[2];
  P.logdt = (const __nv_bfloat16*)d_in[7];
  P.dskip = (const __nv_bfloat16*)d_in[8];
  P.brep = (const __nv_bfloat16*)d_in[3];
  P.bimp = (const __nv_bfloat16*)d_in[4];
  P.kp = (const __nv_bfloat16*)d_in[10];
  P.vp = (const __nv_bfloat16*)d_in[11];
  P.shk = (const __nv_bfloat16*)d_in[12];
  P.ssmk = (const __nv_bfloat16*)d_in[13];
  P.ssmd = (const __nv_bfloat16*)d_in[14];
  P.out = (float*)d_out;
  P.zero = 0;
  fused_kernel<<<NA + NB, 384, SMEM_BYTES>>>(P);
}
```

```cpp
#include <cuda_runtime.h>
#include <cuda_bf16.h>
#include <cuda.h>
#include <stdint.h>

constexpr int SEQ = 2048, DM = 640, OUTW = 1280;
constexpr int NA = 80, NB = 50;
constexpr int SMEM_BYTES = 232448;

template<int N, int TA, int TB, int SA, int SB> struct WSS;
template<int TA, int TB, int SA, int SB> struct WSS<128,TA,TB,SA,SB> {
  static __device__ __forceinline__ void run(float* d, uint32_t da, uint32_t db, int sc) {
    asm volatile("{\n.reg .pred p;\n.reg .b64 da, db;\nmov.b64 da, {%64, %71};\nmov.b64 db, {%65, %71};\nsetp.ne.b32 p, %66, 0;\nwgmma.mma_async.sync.aligned.m64n128k16.f32.bf16.bf16 {%0, %1, %2, %3, %4, %5, %6, %7, %8, %9, %10, %11, %12, %13, %14, %15, %16, %17, %18, %19, %20, %21, %22, %23, %24, %25, %26, %27, %28, %29, %30, %31, %32, %33, %34, %35, %36, %37, %38, %39, %40, %41, %42, %43, %44, %45, %46, %47, %48, %49, %50, %51, %52, %53, %54, %55, %56, %57, %58, %59, %60, %61, %62, %63}, da, db, p, %67, %68, %69, %70;\n}\n"
      : "+f"(d[0]), "+f"(d[1]), "+f"(d[2]), "+f"(d[3]), "+f"(d[4]), "+f"(d[5]), "+f"(d[6]), "+f"(d[7]), "+f"(d[8]), "+f"(d[9]), "+f"(d[10]), "+f"(d[11]), "+f"(d[12]), "+f"(d[13]), "+f"(d[14]), "+f"(d[15]), "+f"(d[16]), "+f"(d[17]), "+f"(d[18]), "+f"(d[19]), "+f"(d[20]), "+f"(d[21]), "+f"(d[22]), "+f"(d[23]), "+f"(d[24]), "+f"(d[25]), "+f"(d[26]), "+f"(d[27]), "+f"(d[28]), "+f"(d[29]), "+f"(d[30]), "+f"(d[31]), "+f"(d[32]), "+f"(d[33]), "+f"(d[34]), "+f"(d[35]), "+f"(d[36]), "+f"(d[37]), "+f"(d[38]), "+f"(d[39]), "+f"(d[40]), "+f"(d[41]), "+f"(d[42]), "+f"(d[43]), "+f"(d[44]), "+f"(d[45]), "+f"(d[46]), "+f"(d[47]), "+f"(d[48]), "+f"(d[49]), "+f"(d[50]), "+f"(d[51]), "+f"(d[52]), "+f"(d[53]), "+f"(d[54]), "+f"(d[55]), "+f"(d[56]), "+f"(d[57]), "+f"(d[58]), "+f"(d[59]), "+f"(d[60]), "+f"(d[61]), "+f"(d[62]), "+f"(d[63]) : "r"(da), "r"(db), "r"(sc), "n"(SA), "n"(SB), "n"(TA), "n"(TB), "n"(0x40000040));
  }
};
template<int N> struct WRS;
template<> struct WRS<8> {
  static __device__ __forceinline__ void run(float* d, uint32_t a0, uint32_t a1, uint32_t a2, uint32_t a3, uint64_t db, int sc) {
    asm volatile("{\n.reg .pred p;\nsetp.ne.b32 p, %9, 0;\nwgmma.mma_async.sync.aligned.m64n8k16.f32.bf16.bf16 {%0, %1, %2, %3}, {%4, %5, %6, %7}, %8, p, 1, 1, 0;\n}\n"
      : "+f"(d[0]), "+f"(d[1]), "+f"(d[2]), "+f"(d[3]) : "r"(a0), "r"(a1), "r"(a2), "r"(a3), "l"(db), "r"(sc));
  }
};
template<> struct WRS<16> {
  static __device__ __forceinline__ void run(float* d, uint32_t a0, uint32_t a1, uint32_t a2, uint32_t a3, uint64_t db, int sc) {
    asm volatile("{\n.reg .pred p;\nsetp.ne.b32 p, %13, 0;\nwgmma.mma_async.sync.aligned.m64n16k16.f32.bf16.bf16 {%0, %1, %2, %3, %4, %5, %6, %7}, {%8, %9, %10, %11}, %12, p, 1, 1, 0;\n}\n"
      : "+f"(d[0]), "+f"(d[1]), "+f"(d[2]), "+f"(d[3]), "+f"(d[4]), "+f"(d[5]), "+f"(d[6]), "+f"(d[7]) : "r"(a0), "r"(a1), "r"(a2), "r"(a3), "l"(db), "r"(sc));
  }
};
template<> struct WRS<24> {
  static __device__ __forceinline__ void run(float* d, uint32_t a0, uint32_t a1, uint32_t a2, uint32_t a3, uint64_t db, int sc) {
    asm volatile("{\n.reg .pred p;\nsetp.ne.b32 p, %17, 0;\nwgmma.mma_async.sync.aligned.m64n24k16.f32.bf16.bf16 {%0, %1, %2, %3, %4, %5, %6, %7, %8, %9, %10, %11}, {%12, %13, %14, %15}, %16, p, 1, 1, 0;\n}\n"
      : "+f"(d[0]), "+f"(d[1]), "+f"(d[2]), "+f"(d[3]), "+f"(d[4]), "+f"(d[5]), "+f"(d[6]), "+f"(d[7]), "+f"(d[8]), "+f"(d[9]), "+f"(d[10]), "+f"(d[11]) : "r"(a0), "r"(a1), "r"(a2), "r"(a3), "l"(db), "r"(sc));
  }
};
template<> struct WRS<32> {
  static __device__ __forceinline__ void run(float* d, uint32_t a0, uint32_t a1, uint32_t a2, uint32_t a3, uint64_t db, int sc) {
    asm volatile("{\n.reg .pred p;\nsetp.ne.b32 p, %21, 0;\nwgmma.mma_async.sync.aligned.m64n32k16.f32.bf16.bf16 {%0, %1, %2, %3, %4, %5, %6, %7, %8, %9, %10, %11, %12, %13, %14, %15}, {%16, %17, %18, %19}, %20, p, 1, 1, 0;\n}\n"
      : "+f"(d[0]), "+f"(d[1]), "+f"(d[2]), "+f"(d[3]), "+f"(d[4]), "+f"(d[5]), "+f"(d[6]), "+f"(d[7]), "+f"(d[8]), "+f"(d[9]), "+f"(d[10]), "+f"(d[11]), "+f"(d[12]), "+f"(d[13]), "+f"(d[14]), "+f"(d[15]) : "r"(a0), "r"(a1), "r"(a2), "r"(a3), "l"(db), "r"(sc));
  }
};
template<> struct WRS<40> {
  static __device__ __forceinline__ void run(float* d, uint32_t a0, uint32_t a1, uint32_t a2, uint32_t a3, uint64_t db, int sc) {
    asm volatile("{\n.reg .pred p;\nsetp.ne.b32 p, %25, 0;\nwgmma.mma_async.sync.aligned.m64n40k16.f32.bf16.bf16 {%0, %1, %2, %3, %4, %5, %6, %7, %8, %9, %10, %11, %12, %13, %14, %15, %16, %17, %18, %19}, {%20, %21, %22, %23}, %24, p, 1, 1, 0;\n}\n"
      : "+f"(d[0]), "+f"(d[1]), "+f"(d[2]), "+f"(d[3]), "+f"(d[4]), "+f"(d[5]), "+f"(d[6]), "+f"(d[7]), "+f"(d[8]), "+f"(d[9]), "+f"(d[10]), "+f"(d[11]), "+f"(d[12]), "+f"(d[13]), "+f"(d[14]), "+f"(d[15]), "+f"(d[16]), "+f"(d[17]), "+f"(d[18]), "+f"(d[19]) : "r"(a0), "r"(a1), "r"(a2), "r"(a3), "l"(db), "r"(sc));
  }
};
template<> struct WRS<48> {
  static __device__ __forceinline__ void run(float* d, uint32_t a0, uint32_t a1, uint32_t a2, uint32_t a3, uint64_t db, int sc) {
    asm volatile("{\n.reg .pred p;\nsetp.ne.b32 p, %29, 0;\nwgmma.mma_async.sync.aligned.m64n48k16.f32.bf16.bf16 {%0, %1, %2, %3, %4, %5, %6, %7, %8, %9, %10, %11, %12, %13, %14, %15, %16, %17, %18, %19, %20, %21, %22, %23}, {%24, %25, %26, %27}, %28, p, 1, 1, 0;\n}\n"
      : "+f"(d[0]), "+f"(d[1]), "+f"(d[2]), "+f"(d[3]), "+f"(d[4]), "+f"(d[5]), "+f"(d[6]), "+f"(d[7]), "+f"(d[8]), "+f"(d[9]), "+f"(d[10]), "+f"(d[11]), "+f"(d[12]), "+f"(d[13]), "+f"(d[14]), "+f"(d[15]), "+f"(d[16]), "+f"(d[17]), "+f"(d[18]), "+f"(d[19]), "+f"(d[20]), "+f"(d[21]), "+f"(d[22]), "+f"(d[23]) : "r"(a0), "r"(a1), "r"(a2), "r"(a3), "l"(db), "r"(sc));
  }
};
template<> struct WRS<56> {
  static __device__ __forceinline__ void run(float* d, uint32_t a0, uint32_t a1, uint32_t a2, uint32_t a3, uint64_t db, int sc) {
    asm volatile("{\n.reg .pred p;\nsetp.ne.b32 p, %33, 0;\nwgmma.mma_async.sync.aligned.m64n56k16.f32.bf16.bf16 {%0, %1, %2, %3, %4, %5, %6, %7, %8, %9, %10, %11, %12, %13, %14, %15, %16, %17, %18, %19, %20, %21, %22, %23, %24, %25, %26, %27}, {%28, %29, %30, %31}, %32, p, 1, 1, 0;\n}\n"
      : "+f"(d[0]), "+f"(d[1]), "+f"(d[2]), "+f"(d[3]), "+f"(d[4]), "+f"(d[5]), "+f"(d[6]), "+f"(d[7]), "+f"(d[8]), "+f"(d[9]), "+f"(d[10]), "+f"(d[11]), "+f"(d[12]), "+f"(d[13]), "+f"(d[14]), "+f"(d[15]), "+f"(d[16]), "+f"(d[17]), "+f"(d[18]), "+f"(d[19]), "+f"(d[20]), "+f"(d[21]), "+f"(d[22]), "+f"(d[23]), "+f"(d[24]), "+f"(d[25]), "+f"(d[26]), "+f"(d[27]) : "r"(a0), "r"(a1), "r"(a2), "r"(a3), "l"(db), "r"(sc));
  }
};
template<> struct WRS<64> {
  static __device__ __forceinline__ void run(float* d, uint32_t a0, uint32_t a1, uint32_t a2, uint32_t a3, uint64_t db, int sc) {
    asm volatile("{\n.reg .pred p;\nsetp.ne.b32 p, %37, 0;\nwgmma.mma_async.sync.aligned.m64n64k16.f32.bf16.bf16 {%0, %1, %2, %3, %4, %5, %6, %7, %8, %9, %10, %11, %12, %13, %14, %15, %16, %17, %18, %19, %20, %21, %22, %23, %24, %25, %26, %27, %28, %29, %30, %31}, {%32, %33, %34, %35}, %36, p, 1, 1, 0;\n}\n"
      : "+f"(d[0]), "+f"(d[1]), "+f"(d[2]), "+f"(d[3]), "+f"(d[4]), "+f"(d[5]), "+f"(d[6]), "+f"(d[7]), "+f"(d[8]), "+f"(d[9]), "+f"(d[10]), "+f"(d[11]), "+f"(d[12]), "+f"(d[13]), "+f"(d[14]), "+f"(d[15]), "+f"(d[16]), "+f"(d[17]), "+f"(d[18]), "+f"(d[19]), "+f"(d[20]), "+f"(d[21]), "+f"(d[22]), "+f"(d[23]), "+f"(d[24]), "+f"(d[25]), "+f"(d[26]), "+f"(d[27]), "+f"(d[28]), "+f"(d[29]), "+f"(d[30]), "+f"(d[31]) : "r"(a0), "r"(a1), "r"(a2), "r"(a3), "l"(db), "r"(sc));
  }
};
template<> struct WRS<72> {
  static __device__ __forceinline__ void run(float* d, uint32_t a0, uint32_t a1, uint32_t a2, uint32_t a3, uint64_t db, int sc) {
    asm volatile("{\n.reg .pred p;\nsetp.ne.b32 p, %41, 0;\nwgmma.mma_async.sync.aligned.m64n72k16.f32.bf16.bf16 {%0, %1, %2, %3, %4, %5, %6, %7, %8, %9, %10, %11, %12, %13, %14, %15, %16, %17, %18, %19, %20, %21, %22, %23, %24, %25, %26, %27, %28, %29, %30, %31, %32, %33, %34, %35}, {%36, %37, %38, %39}, %40, p, 1, 1, 0;\n}\n"
      : "+f"(d[0]), "+f"(d[1]), "+f"(d[2]), "+f"(d[3]), "+f"(d[4]), "+f"(d[5]), "+f"(d[6]), "+f"(d[7]), "+f"(d[8]), "+f"(d[9]), "+f"(d[10]), "+f"(d[11]), "+f"(d[12]), "+f"(d[13]), "+f"(d[14]), "+f"(d[15]), "+f"(d[16]), "+f"(d[17]), "+f"(d[18]), "+f"(d[19]), "+f"(d[20]), "+f"(d[21]), "+f"(d[22]), "+f"(d[23]), "+f"(d[24]), "+f"(d[25]), "+f"(d[26]), "+f"(d[27]), "+f"(d[28]), "+f"(d[29]), "+f"(d[30]), "+f"(d[31]), "+f"(d[32]), "+f"(d[33]), "+f"(d[34]), "+f"(d[35]) : "r"(a0), "r"(a1), "r"(a2), "r"(a3), "l"(db), "r"(sc));
  }
};
template<> struct WRS<80> {
  static __device__ __forceinline__ void run(float* d, uint32_t a0, uint32_t a1, uint32_t a2, uint32_t a3, uint64_t db, int sc) {
    asm volatile("{\n.reg .pred p;\nsetp.ne.b32 p, %45, 0;\nwgmma.mma_async.sync.aligned.m64n80k16.f32.bf16.bf16 {%0, %1, %2, %3, %4, %5, %6, %7, %8, %9, %10, %11, %12, %13, %14, %15, %16, %17, %18, %19, %20, %21, %22, %23, %24, %25, %26, %27, %28, %29, %30, %31, %32, %33, %34, %35, %36, %37, %38, %39}, {%40, %41, %42, %43}, %44, p, 1, 1, 0;\n}\n"
      : "+f"(d[0]), "+f"(d[1]), "+f"(d[2]), "+f"(d[3]), "+f"(d[4]), "+f"(d[5]), "+f"(d[6]), "+f"(d[7]), "+f"(d[8]), "+f"(d[9]), "+f"(d[10]), "+f"(d[11]), "+f"(d[12]), "+f"(d[13]), "+f"(d[14]), "+f"(d[15]), "+f"(d[16]), "+f"(d[17]), "+f"(d[18]), "+f"(d[19]), "+f"(d[20]), "+f"(d[21]), "+f"(d[22]), "+f"(d[23]), "+f"(d[24]), "+f"(d[25]), "+f"(d[26]), "+f"(d[27]), "+f"(d[28]), "+f"(d[29]), "+f"(d[30]), "+f"(d[31]), "+f"(d[32]), "+f"(d[33]), "+f"(d[34]), "+f"(d[35]), "+f"(d[36]), "+f"(d[37]), "+f"(d[38]), "+f"(d[39]) : "r"(a0), "r"(a1), "r"(a2), "r"(a3), "l"(db), "r"(sc));
  }
};
template<> struct WRS<88> {
  static __device__ __forceinline__ void run(float* d, uint32_t a0, uint32_t a1, uint32_t a2, uint32_t a3, uint64_t db, int sc) {
    asm volatile("{\n.reg .pred p;\nsetp.ne.b32 p, %49, 0;\nwgmma.mma_async.sync.aligned.m64n88k16.f32.bf16.bf16 {%0, %1, %2, %3, %4, %5, %6, %7, %8, %9, %10, %11, %12, %13, %14, %15, %16, %17, %18, %19, %20, %21, %22, %23, %24, %25, %26, %27, %28, %29, %30, %31, %32, %33, %34, %35, %36, %37, %38, %39, %40, %41, %42, %43}, {%44, %45, %46, %47}, %48, p, 1, 1, 0;\n}\n"
      : "+f"(d[0]), "+f"(d[1]), "+f"(d[2]), "+f"(d[3]), "+f"(d[4]), "+f"(d[5]), "+f"(d[6]), "+f"(d[7]), "+f"(d[8]), "+f"(d[9]), "+f"(d[10]), "+f"(d[11]), "+f"(d[12]), "+f"(d[13]), "+f"(d[14]), "+f"(d[15]), "+f"(d[16]), "+f"(d[17]), "+f"(d[18]), "+f"(d[19]), "+f"(d[20]), "+f"(d[21]), "+f"(d[22]), "+f"(d[23]), "+f"(d[24]), "+f"(d[25]), "+f"(d[26]), "+f"(d[27]), "+f"(d[28]), "+f"(d[29]), "+f"(d[30]), "+f"(d[31]), "+f"(d[32]), "+f"(d[33]), "+f"(d[34]), "+f"(d[35]), "+f"(d[36]), "+f"(d[37]), "+f"(d[38]), "+f"(d[39]), "+f"(d[40]), "+f"(d[41]), "+f"(d[42]), "+f"(d[43]) : "r"(a0), "r"(a1), "r"(a2), "r"(a3), "l"(db), "r"(sc));
  }
};
template<> struct WRS<96> {
  static __device__ __forceinline__ void run(float* d, uint32_t a0, uint32_t a1, uint32_t a2, uint32_t a3, uint64_t db, int sc) {
    asm volatile("{\n.reg .pred p;\nsetp.ne.b32 p, %53, 0;\nwgmma.mma_async.sync.aligned.m64n96k16.f32.bf16.bf16 {%0, %1, %2, %3, %4, %5, %6, %7, %8, %9, %10, %11, %12, %13, %14, %15, %16, %17, %18, %19, %20, %21, %22, %23, %24, %25, %26, %27, %28, %29, %30, %31, %32, %33, %34, %35, %36, %37, %38, %39, %40, %41, %42, %43, %44, %45, %46, %47}, {%48, %49, %50, %51}, %52, p, 1, 1, 0;\n}\n"
      : "+f"(d[0]), "+f"(d[1]), "+f"(d[2]), "+f"(d[3]), "+f"(d[4]), "+f"(d[5]), "+f"(d[6]), "+f"(d[7]), "+f"(d[8]), "+f"(d[9]), "+f"(d[10]), "+f"(d[11]), "+f"(d[12]), "+f"(d[13]), "+f"(d[14]), "+f"(d[15]), "+f"(d[16]), "+f"(d[17]), "+f"(d[18]), "+f"(d[19]), "+f"(d[20]), "+f"(d[21]), "+f"(d[22]), "+f"(d[23]), "+f"(d[24]), "+f"(d[25]), "+f"(d[26]), "+f"(d[27]), "+f"(d[28]), "+f"(d[29]), "+f"(d[30]), "+f"(d[31]), "+f"(d[32]), "+f"(d[33]), "+f"(d[34]), "+f"(d[35]), "+f"(d[36]), "+f"(d[37]), "+f"(d[38]), "+f"(d[39]), "+f"(d[40]), "+f"(d[41]), "+f"(d[42]), "+f"(d[43]), "+f"(d[44]), "+f"(d[45]), "+f"(d[46]), "+f"(d[47]) : "r"(a0), "r"(a1), "r"(a2), "r"(a3), "l"(db), "r"(sc));
  }
};
template<> struct WRS<104> {
  static __device__ __forceinline__ void run(float* d, uint32_t a0, uint32_t a1, uint32_t a2, uint32_t a3, uint64_t db, int sc) {
    asm volatile("{\n.reg .pred p;\nsetp.ne.b32 p, %57, 0;\nwgmma.mma_async.sync.aligned.m64n104k16.f32.bf16.bf16 {%0, %1, %2, %3, %4, %5, %6, %7, %8, %9, %10, %11, %12, %13, %14, %15, %16, %17, %18, %19, %20, %21, %22, %23, %24, %25, %26, %27, %28, %29, %30, %31, %32, %33, %34, %35, %36, %37, %38, %39, %40, %41, %42, %43, %44, %45, %46, %47, %48, %49, %50, %51}, {%52, %53, %54, %55}, %56, p, 1, 1, 0;\n}\n"
      : "+f"(d[0]), "+f"(d[1]), "+f"(d[2]), "+f"(d[3]), "+f"(d[4]), "+f"(d[5]), "+f"(d[6]), "+f"(d[7]), "+f"(d[8]), "+f"(d[9]), "+f"(d[10]), "+f"(d[11]), "+f"(d[12]), "+f"(d[13]), "+f"(d[14]), "+f"(d[15]), "+f"(d[16]), "+f"(d[17]), "+f"(d[18]), "+f"(d[19]), "+f"(d[20]), "+f"(d[21]), "+f"(d[22]), "+f"(d[23]), "+f"(d[24]), "+f"(d[25]), "+f"(d[26]), "+f"(d[27]), "+f"(d[28]), "+f"(d[29]), "+f"(d[30]), "+f"(d[31]), "+f"(d[32]), "+f"(d[33]), "+f"(d[34]), "+f"(d[35]), "+f"(d[36]), "+f"(d[37]), "+f"(d[38]), "+f"(d[39]), "+f"(d[40]), "+f"(d[41]), "+f"(d[42]), "+f"(d[43]), "+f"(d[44]), "+f"(d[45]), "+f"(d[46]), "+f"(d[47]), "+f"(d[48]), "+f"(d[49]), "+f"(d[50]), "+f"(d[51]) : "r"(a0), "r"(a1), "r"(a2), "r"(a3), "l"(db), "r"(sc));
  }
};
template<> struct WRS<112> {
  static __device__ __forceinline__ void run(float* d, uint32_t a0, uint32_t a1, uint32_t a2, uint32_t a3, uint64_t db, int sc) {
    asm volatile("{\n.reg .pred p;\nsetp.ne.b32 p, %61, 0;\nwgmma.mma_async.sync.aligned.m64n112k16.f32.bf16.bf16 {%0, %1, %2, %3, %4, %5, %6, %7, %8, %9, %10, %11, %12, %13, %14, %15, %16, %17, %18, %19, %20, %21, %22, %23, %24, %25, %26, %27, %28, %29, %30, %31, %32, %33, %34, %35, %36, %37, %38, %39, %40, %41, %42, %43, %44, %45, %46, %47, %48, %49, %50, %51, %52, %53, %54, %55}, {%56, %57, %58, %59}, %60, p, 1, 1, 0;\n}\n"
      : "+f"(d[0]), "+f"(d[1]), "+f"(d[2]), "+f"(d[3]), "+f"(d[4]), "+f"(d[5]), "+f"(d[6]), "+f"(d[7]), "+f"(d[8]), "+f"(d[9]), "+f"(d[10]), "+f"(d[11]), "+f"(d[12]), "+f"(d[13]), "+f"(d[14]), "+f"(d[15]), "+f"(d[16]), "+f"(d[17]), "+f"(d[18]), "+f"(d[19]), "+f"(d[20]), "+f"(d[21]), "+f"(d[22]), "+f"(d[23]), "+f"(d[24]), "+f"(d[25]), "+f"(d[26]), "+f"(d[27]), "+f"(d[28]), "+f"(d[29]), "+f"(d[30]), "+f"(d[31]), "+f"(d[32]), "+f"(d[33]), "+f"(d[34]), "+f"(d[35]), "+f"(d[36]), "+f"(d[37]), "+f"(d[38]), "+f"(d[39]), "+f"(d[40]), "+f"(d[41]), "+f"(d[42]), "+f"(d[43]), "+f"(d[44]), "+f"(d[45]), "+f"(d[46]), "+f"(d[47]), "+f"(d[48]), "+f"(d[49]), "+f"(d[50]), "+f"(d[51]), "+f"(d[52]), "+f"(d[53]), "+f"(d[54]), "+f"(d[55]) : "r"(a0), "r"(a1), "r"(a2), "r"(a3), "l"(db), "r"(sc));
  }
};
template<> struct WRS<120> {
  static __device__ __forceinline__ void run(float* d, uint32_t a0, uint32_t a1, uint32_t a2, uint32_t a3, uint64_t db, int sc) {
    asm volatile("{\n.reg .pred p;\nsetp.ne.b32 p, %65, 0;\nwgmma.mma_async.sync.aligned.m64n120k16.f32.bf16.bf16 {%0, %1, %2, %3, %4, %5, %6, %7, %8, %9, %10, %11, %12, %13, %14, %15, %16, %17, %18, %19, %20, %21, %22, %23, %24, %25, %26, %27, %28, %29, %30, %31, %32, %33, %34, %35, %36, %37, %38, %39, %40, %41, %42, %43, %44, %45, %46, %47, %48, %49, %50, %51, %52, %53, %54, %55, %56, %57, %58, %59}, {%60, %61, %62, %63}, %64, p, 1, 1, 0;\n}\n"
      : "+f"(d[0]), "+f"(d[1]), "+f"(d[2]), "+f"(d[3]), "+f"(d[4]), "+f"(d[5]), "+f"(d[6]), "+f"(d[7]), "+f"(d[8]), "+f"(d[9]), "+f"(d[10]), "+f"(d[11]), "+f"(d[12]), "+f"(d[13]), "+f"(d[14]), "+f"(d[15]), "+f"(d[16]), "+f"(d[17]), "+f"(d[18]), "+f"(d[19]), "+f"(d[20]), "+f"(d[21]), "+f"(d[22]), "+f"(d[23]), "+f"(d[24]), "+f"(d[25]), "+f"(d[26]), "+f"(d[27]), "+f"(d[28]), "+f"(d[29]), "+f"(d[30]), "+f"(d[31]), "+f"(d[32]), "+f"(d[33]), "+f"(d[34]), "+f"(d[35]), "+f"(d[36]), "+f"(d[37]), "+f"(d[38]), "+f"(d[39]), "+f"(d[40]), "+f"(d[41]), "+f"(d[42]), "+f"(d[43]), "+f"(d[44]), "+f"(d[45]), "+f"(d[46]), "+f"(d[47]), "+f"(d[48]), "+f"(d[49]), "+f"(d[50]), "+f"(d[51]), "+f"(d[52]), "+f"(d[53]), "+f"(d[54]), "+f"(d[55]), "+f"(d[56]), "+f"(d[57]), "+f"(d[58]), "+f"(d[59]) : "r"(a0), "r"(a1), "r"(a2), "r"(a3), "l"(db), "r"(sc));
  }
};
template<> struct WRS<128> {
  static __device__ __forceinline__ void run(float* d, uint32_t a0, uint32_t a1, uint32_t a2, uint32_t a3, uint64_t db, int sc) {
    asm volatile("{\n.reg .pred p;\nsetp.ne.b32 p, %69, 0;\nwgmma.mma_async.sync.aligned.m64n128k16.f32.bf16.bf16 {%0, %1, %2, %3, %4, %5, %6, %7, %8, %9, %10, %11, %12, %13, %14, %15, %16, %17, %18, %19, %20, %21, %22, %23, %24, %25, %26, %27, %28, %29, %30, %31, %32, %33, %34, %35, %36, %37, %38, %39, %40, %41, %42, %43, %44, %45, %46, %47, %48, %49, %50, %51, %52, %53, %54, %55, %56, %57, %58, %59, %60, %61, %62, %63}, {%64, %65, %66, %67}, %68, p, 1, 1, 0;\n}\n"
      : "+f"(d[0]), "+f"(d[1]), "+f"(d[2]), "+f"(d[3]), "+f"(d[4]), "+f"(d[5]), "+f"(d[6]), "+f"(d[7]), "+f"(d[8]), "+f"(d[9]), "+f"(d[10]), "+f"(d[11]), "+f"(d[12]), "+f"(d[13]), "+f"(d[14]), "+f"(d[15]), "+f"(d[16]), "+f"(d[17]), "+f"(d[18]), "+f"(d[19]), "+f"(d[20]), "+f"(d[21]), "+f"(d[22]), "+f"(d[23]), "+f"(d[24]), "+f"(d[25]), "+f"(d[26]), "+f"(d[27]), "+f"(d[28]), "+f"(d[29]), "+f"(d[30]), "+f"(d[31]), "+f"(d[32]), "+f"(d[33]), "+f"(d[34]), "+f"(d[35]), "+f"(d[36]), "+f"(d[37]), "+f"(d[38]), "+f"(d[39]), "+f"(d[40]), "+f"(d[41]), "+f"(d[42]), "+f"(d[43]), "+f"(d[44]), "+f"(d[45]), "+f"(d[46]), "+f"(d[47]), "+f"(d[48]), "+f"(d[49]), "+f"(d[50]), "+f"(d[51]), "+f"(d[52]), "+f"(d[53]), "+f"(d[54]), "+f"(d[55]), "+f"(d[56]), "+f"(d[57]), "+f"(d[58]), "+f"(d[59]), "+f"(d[60]), "+f"(d[61]), "+f"(d[62]), "+f"(d[63]) : "r"(a0), "r"(a1), "r"(a2), "r"(a3), "l"(db), "r"(sc));
  }
};

__device__ unsigned int g_ticket;
__device__ unsigned int g_flag[16 * 32];
__device__ unsigned int g_zflag[10 * 32];
__device__ uint4 g_Z[10 * 2 * 265];
__device__ unsigned long long g_E[16 * 640];
__device__ uint4 g_H[16 * 20 * 1024];


struct Params {
  CUtensorMap x, bre, bim, cre, cim, k, v, k16, v16, q, q16, oa, ob, oh, o4;
  const __nv_bfloat16 *xp, *lre, *lim, *logdt, *dskip, *brep, *bimp, *kp, *vp, *shk, *ssmk, *ssmd;
  float* out;
  uint32_t zero;
};

__device__ __forceinline__ uint32_t smem_u32(const void* p) { return (uint32_t)__cvta_generic_to_shared(p); }
__device__ __forceinline__ uint32_t mkdesc(uint32_t addr, uint32_t lbo) { return ((addr & 0x3FFFF) >> 4) | ((lbo >> 4) << 16); }
__device__ __forceinline__ void wg_fence() { asm volatile("wgmma.fence.sync.aligned;" ::: "memory"); }
__device__ __forceinline__ void wg_commit() { asm volatile("wgmma.commit_group.sync.aligned;" ::: "memory"); }
template <int N> __device__ __forceinline__ void wg_wait() { asm volatile("wgmma.wait_group.sync.aligned %0;" ::"n"(N) : "memory"); }
__device__ __forceinline__ void mbar_init(uint32_t bar, int cnt) { asm volatile("mbarrier.init.shared::cta.b64 [%0], %1;" ::"r"(bar), "r"(cnt) : "memory"); }
__device__ __forceinline__ void mbar_expect(uint32_t bar, uint32_t bytes) {
  asm volatile("mbarrier.arrive.expect_tx.shared::cta.b64 _, [%0], %1;" ::"r"(bar), "r"(bytes) : "memory");
}
__device__ __forceinline__ void mbar_arrive(uint32_t bar) { asm volatile("mbarrier.arrive.shared::cta.b64 _, [%0];" ::"r"(bar) : "memory"); }
__device__ __forceinline__ void mbar_wait(uint32_t bar, uint32_t parity) {
  asm volatile(
      "{\n.reg .pred p;\n.reg .u32 c;\nmov.u32 c, 0;\n"
      "L1_%=:\nmbarrier.try_wait.parity.shared::cta.b64 p, [%0], %1;\n@p bra L2_%=;\n"
      "add.u32 c, c, 1;\nsetp.lt.u32 p, c, 2000000;\n@p bra L1_%=;\ntrap;\nL2_%=:\n}" ::"r"(bar), "r"(parity) : "memory");
}
__device__ __forceinline__ void mbar_wait_bg(uint32_t bar, uint32_t parity) {
  asm volatile(
      "{\n.reg .pred p;\n.reg .u32 c;\nmov.u32 c, 0;\n"
      "L1_%=:\nmbarrier.try_wait.parity.shared::cta.b64 p, [%0], %1, 4000;\n@p bra L2_%=;\n"
      "add.u32 c, c, 1;\nsetp.lt.u32 p, c, 200000;\n@p bra L1_%=;\ntrap;\nL2_%=:\n}" ::"r"(bar), "r"(parity) : "memory");
}
__device__ __forceinline__ void tma2d(uint32_t dst, const CUtensorMap* m, int c0, int c1, uint32_t bar) {
  asm volatile("cp.async.bulk.tensor.2d.shared::cluster.global.mbarrier::complete_tx::bytes [%0], [%1, {%3, %4}], [%2];" ::"r"(dst),
               "l"(m), "r"(bar), "r"(c0), "r"(c1) : "memory");
}
__device__ __forceinline__ void tma3d(uint32_t dst, const CUtensorMap* m, int c0, int c1, int c2, uint32_t bar) {
  asm volatile("cp.async.bulk.tensor.3d.shared::cluster.global.mbarrier::complete_tx::bytes [%0], [%1, {%3, %4, %5}], [%2];" ::"r"(dst),
               "l"(m), "r"(bar), "r"(c0), "r"(c1), "r"(c2) : "memory");
}
__device__ __forceinline__ void tma5d(uint32_t dst, const CUtensorMap* m, int c0, int c4, uint32_t bar) {
  asm volatile("cp.async.bulk.tensor.5d.shared::cluster.global.mbarrier::complete_tx::bytes [%0], [%1, {%3, %4, %4, %4, %5}], [%2];" ::"r"(dst),
               "l"(m), "r"(bar), "r"(c0), "r"(0), "r"(c4) : "memory");
}
__device__ __forceinline__ void tma5d_store(const CUtensorMap* m, uint32_t src, int c0, int c3, int c4) {
  asm volatile("cp.async.bulk.tensor.5d.global.shared::cta.bulk_group [%0, {%2, %3, %3, %4, %5}], [%1];" ::"l"(m), "r"(src), "r"(c0), "r"(0), "r"(c3), "r"(c4) : "memory");
}
__device__ __forceinline__ void bulk_g2s(uint32_t dst, const void* src, uint32_t bytes, uint32_t bar) {
  asm volatile("cp.async.bulk.shared::cluster.global.mbarrier::complete_tx::bytes [%0], [%1], %2, [%3];" ::"r"(dst), "l"(src), "r"(bytes), "r"(bar) : "memory");
}
__device__ __forceinline__ void bulk_s2g(void* dst, uint32_t src, uint32_t bytes) {
  asm volatile("cp.async.bulk.global.shared::cta.bulk_group [%0], [%1], %2;" ::"l"(dst), "r"(src), "r"(bytes) : "memory");
}
__device__ __forceinline__ void prefetch_tmap(const CUtensorMap* m) { asm volatile("prefetch.tensormap [%0];" ::"l"(m) : "memory"); }
__device__ __forceinline__ void fence_async_smem() { asm volatile("fence.proxy.async.shared::cta;" ::: "memory"); }
__device__ __forceinline__ void bar_sync(int id, int n) { asm volatile("bar.sync %0, %1;" ::"r"(id), "r"(n) : "memory"); }
__device__ __forceinline__ void bar_arrive(int id, int n) { asm volatile("bar.arrive %0, %1;" ::"r"(id), "r"(n) : "memory"); }
__device__ __forceinline__ uint2 lds64(uint32_t a) { uint2 r; asm volatile("ld.shared.v2.u32 {%0,%1}, [%2];" : "=r"(r.x), "=r"(r.y) : "r"(a) : "memory"); return r; }
__device__ __forceinline__ uint32_t pack_bf16(float lo, float hi) {
  uint32_t r; asm("cvt.rn.bf16x2.f32 %0, %1, %2;" : "=r"(r) : "f"(hi), "f"(lo)); return r;
}
__device__ __forceinline__ uint32_t bmul2(uint32_t a, uint32_t b) { uint32_t r; asm("mul.rn.bf16x2 %0, %1, %2;" : "=r"(r) : "r"(a), "r"(b)); return r; }
__device__ __forceinline__ uint32_t badd2(uint32_t a, uint32_t b) { uint32_t r; asm("add.rn.bf16x2 %0, %1, %2;" : "=r"(r) : "r"(a), "r"(b)); return r; }
__device__ __forceinline__ float bf_lo(uint32_t v) { return __uint_as_float(v << 16); }
__device__ __forceinline__ float bf_hi(uint32_t v) { return __uint_as_float(v & 0xffff0000u); }
__device__ __forceinline__ void stsm4(uint32_t a, uint32_t r0, uint32_t r1, uint32_t r2, uint32_t r3) {
  asm volatile("stmatrix.sync.aligned.m8n8.x4.shared.b16 [%0], {%1,%2,%3,%4};" ::"r"(a), "r"(r0), "r"(r1), "r"(r2), "r"(r3) : "memory");
}
__device__ __forceinline__ void stsm4t(uint32_t a, uint32_t r0, uint32_t r1, uint32_t r2, uint32_t r3) {
  asm volatile("stmatrix.sync.aligned.m8n8.x4.trans.shared.b16 [%0], {%1,%2,%3,%4};" ::"r"(a), "r"(r0), "r"(r1), "r"(r2), "r"(r3) : "memory");
}
__device__ __forceinline__ void ldsm4(uint32_t a, uint32_t* r) {
  asm volatile("ldmatrix.sync.aligned.m8n8.x4.shared.b16 {%0,%1,%2,%3}, [%4];" : "=r"(r[0]), "=r"(r[1]), "=r"(r[2]), "=r"(r[3]) : "r"(a) : "memory");
}
__device__ __forceinline__ void ldsm4t(uint32_t a, uint32_t* r) {
  asm volatile("ldmatrix.sync.aligned.m8n8.x4.trans.shared.b16 {%0,%1,%2,%3}, [%4];" : "=r"(r[0]), "=r"(r[1]), "=r"(r[2]), "=r"(r[3]) : "r"(a) : "memory");
}
__device__ __forceinline__ uint32_t lds32(uint32_t a) { uint32_t r; asm volatile("ld.shared.u32 %0, [%1];" : "=r"(r) : "r"(a) : "memory"); return r; }
__device__ __forceinline__ float2 lds64f(uint32_t a) { float2 r; asm volatile("ld.shared.v2.f32 {%0,%1}, [%2];" : "=f"(r.x), "=f"(r.y) : "r"(a) : "memory"); return r; }
__device__ __forceinline__ uint4 lds128(uint32_t a) {
  uint4 r; asm volatile("ld.shared.v4.u32 {%0,%1,%2,%3}, [%4];" : "=r"(r.x), "=r"(r.y), "=r"(r.z), "=r"(r.w) : "r"(a) : "memory"); return r;
}
__device__ __forceinline__ void sts32(uint32_t a, uint32_t v) { asm volatile("st.shared.u32 [%0], %1;" ::"r"(a), "r"(v) : "memory"); }
__device__ __forceinline__ void sts64f(uint32_t a, float x, float y) { asm volatile("st.shared.v2.f32 [%0], {%1,%2};" ::"r"(a), "f"(x), "f"(y) : "memory"); }
__device__ __forceinline__ void sts128(uint32_t a, uint32_t x, uint32_t y, uint32_t z, uint32_t w) {
  asm volatile("st.shared.v4.u32 [%0], {%1,%2,%3,%4};" ::"r"(a), "r"(x), "r"(y), "r"(z), "r"(w) : "memory");
}
__device__ __forceinline__ float bf2f(const __nv_bfloat16* p) { return __bfloat162float(*p); }
template <int N> __device__ __forceinline__ void fence_regs(float* a) {
#pragma unroll
  for (int i = 0; i < N; i++) asm volatile("" : "+f"(a[i])::"memory");
}
struct cf { float r, i; };
__device__ __forceinline__ cf cmul(cf a, cf b) { cf o; o.r = a.r * b.r - a.i * b.i; o.i = a.r * b.i + a.i * b.r; return o; }
__device__ __forceinline__ cf cfma(cf a, cf b, cf c) {
  cf o; o.r = fmaf(a.r, b.r, fmaf(-a.i, b.i, c.r)); o.i = fmaf(a.r, b.i, fmaf(a.i, b.r, c.i)); return o;
}
__device__ __forceinline__ cf cshfl_up(cf a, int d) { cf o; o.r = __shfl_up_sync(0xffffffffu, a.r, d, 4); o.i = __shfl_up_sync(0xffffffffu, a.i, d, 4); return o; }
__device__ __forceinline__ uint32_t mapa(uint32_t addr, uint32_t rank) {
  uint32_t r; asm volatile("mapa.shared::cluster.u32 %0, %1, %2;" : "=r"(r) : "r"(addr), "r"(rank)); return r;
}
__device__ __forceinline__ void mbar_arrive_cluster(uint32_t bar) { asm volatile("mbarrier.arrive.shared::cluster.b64 _, [%0];" ::"r"(bar) : "memory"); }
__device__ __forceinline__ void mbar_arrive_p(uint32_t bar, bool p) {
  asm volatile("{\n.reg .pred p;\nsetp.ne.u32 p, %1, 0;\n@p mbarrier.arrive.shared::cta.b64 _, [%0];\n}" ::"r"(bar), "r"((uint32_t)p) : "memory");
}
__device__ __forceinline__ void mbar_arrive_cluster_p(uint32_t bar, bool p) {
  asm volatile("{\n.reg .pred p;\nsetp.ne.u32 p, %1, 0;\n@p mbarrier.arrive.shared::cluster.b64 _, [%0];\n}" ::"r"(bar), "r"((uint32_t)p) : "memory");
}
__device__ __forceinline__ void tma2d_mc(uint32_t dst, const CUtensorMap* m, int c0, int c1, uint32_t bar) {
  asm volatile("cp.async.bulk.tensor.2d.shared::cluster.global.mbarrier::complete_tx::bytes.multicast::cluster [%0], [%1, {%3, %4}], [%2], %5;" ::"r"(dst),
               "l"(m), "r"(bar), "r"(c0), "r"(c1), "h"((uint16_t)3) : "memory");
}
__device__ __forceinline__ void sts128_cluster(uint32_t a, uint32_t x, uint32_t y, uint32_t z, uint32_t w) {
  asm volatile("st.shared::cluster.v4.u32 [%0], {%1,%2,%3,%4};" ::"r"(a), "r"(x), "r"(y), "r"(z), "r"(w) : "memory");
}
__device__ __forceinline__ void cluster_arrive_relaxed() { asm volatile("barrier.cluster.arrive.relaxed.aligned;" ::: "memory"); }
__device__ __forceinline__ void cluster_arrive_release() { asm volatile("barrier.cluster.arrive.release.aligned;" ::: "memory"); }
__device__ __forceinline__ void cluster_wait() { asm volatile("barrier.cluster.wait.acquire.aligned;" ::: "memory"); }
__device__ __forceinline__ void sts128f(uint32_t a, float x, float y, float z, float w) {
  asm volatile("st.shared.v4.f32 [%0], {%1,%2,%3,%4};" ::"r"(a), "f"(x), "f"(y), "f"(z), "f"(w) : "memory");
}

constexpr uint32_t SLOT = 16384;
constexpr uint32_t A_BAR = 14 * SLOT;
constexpr uint32_t A_G1F = A_BAR, A_G1E = A_BAR + 32, A_CF = A_BAR + 64, A_CE = A_BAR + 96, A_HF = A_BAR + 128, A_HE = A_BAR + 160,
                   A_G1D = A_BAR + 192, A_EPB = A_BAR + 200, A_XF = A_BAR + 208, A_HS = A_BAR + 216  , A_TKB = A_BAR + 248,
                   A_EPV = A_BAR + 256, A_HD = A_BAR + 264, A_SB = A_BAR + 272  , A_PO = A_BAR + 2592  , A_DSK = A_BAR + 288  ,
                   A_TAB = A_BAR + 544;
__host__ __device__ constexpr uint32_t cslot(int i) { return (6 + i) * SLOT; }
__host__ __device__ constexpr uint32_t hslot(int i) { return (i < 2 ? 10 + i : (i - 2) * 3) * SLOT; }

__device__ __forceinline__ void a_issue_stage(const Params& P, uint32_t sb, int kb, int pg, int tt) {
  const int s = kb & 3;
  const uint32_t bar = sb + A_G1F + 8 * s, st = sb + 3 * s * SLOT;
  mbar_expect(bar, 3 * SLOT);
  tma5d(st, &P.x, kb * 64, tt, bar);
  tma2d(st + SLOT, &P.bre, kb * 64, pg * 128, bar);
  tma2d(st + 2 * SLOT, &P.bim, kb * 64, pg * 128, bar);
}
__device__ __forceinline__ int k2_block(int ci, int pg) {
  if (ci < 4) return pg * 4 + ci;
  int g = pg + 1 + (ci & 3); if (g >= 5) g -= 5;
  return g * 4 + ((ci - 4) >> 2);
}

__device__ __forceinline__ void roleA_prod(const Params& P, uint32_t sb, int cta) {
  const int tid = threadIdx.x, warp = __shfl_sync(0xffffffffu, tid >> 5, 0), lane = tid & 31;
  const int pg = cta >> 4, tt = cta & 15, rank = cta & 1;
  {
    asm volatile("setmaxnreg.dec.sync.aligned.u32 88;");
    if (warp == 8) {
      if (lane == 0) { a_issue_stage(P, sb, 2, pg, tt); a_issue_stage(P, sb, 3, pg, tt); }
    }
    if (warp == 9 && lane == 0) {
      for (int i = 0; i < 4; i++) {
        mbar_init(sb + A_G1E + 8 * i, 2);
        mbar_init(sb + A_CF + 8 * i, 1); mbar_init(sb + A_CE + 8 * i, 4);
        mbar_init(sb + A_HF + 8 * i, 1); mbar_init(sb + A_HE + 8 * i, 2);
        mbar_init(sb + A_HS + 8 * i, 128);
      }
      mbar_init(sb + A_G1D, 256); mbar_init(sb + A_EPB, 64); mbar_init(sb + A_XF, 1); mbar_init(sb + A_TKB, 1); mbar_init(sb + A_HD, 2);
      mbar_init(sb + A_SB, 32); mbar_init(sb + A_SB + 8, 32); mbar_init(sb + A_PO, 1);
      asm volatile("fence.mbarrier_init.release.cluster;" ::: "memory");
    }
    __syncwarp();
    cluster_arrive_relaxed();
    if (warp != 8) bar_sync(0, 384);
    if (warp == 8) {
      cluster_wait();
      for (int kb = 4; kb < 10; kb++) {
        const int s = kb & 3;
        mbar_wait(sb + A_G1E + 8 * s, ((kb >> 2) - 1) & 1);
        if (lane == 0) a_issue_stage(P, sb, kb, pg, tt);
        __syncwarp();
      }
      if (lane == 0) {
        mbar_expect(sb + A_XF, 2 * SLOT);
        tma5d(sb + 12 * SLOT, &P.x, pg * 128, tt, sb + A_XF);
        tma5d(sb + 13 * SLOT, &P.x, pg * 128 + 64, tt, sb + A_XF);
      }
      __syncwarp();
      for (int ci = 0; ci < 20; ci++) {
        const int ring = ci & 3;
        mbar_wait(sb + A_CE + 8 * ring, (ci >> 2) & 1);
        if (lane == 0) {
          const int blk = k2_block(ci, pg);
          const uint32_t bar = sb + A_CF + 8 * ring;
          mbar_expect(bar, SLOT);
          tma2d_mc(sb + cslot(ring) + rank * 8192, (blk & 1) ? &P.cim : &P.cre, (blk >> 1) * 64, pg * 128 + rank * 64, bar);
        }
        __syncwarp();
      }
    } else if (warp == 9) {
      cluster_wait();
      mbar_wait(sb + A_TKB, 0);
      const uint32_t epoch = lds32(sb + A_EPV);
      mbar_wait(sb + A_G1D, 0);
      uint32_t ready = 0;
      const unsigned int* fp = &g_flag[tt * 32 + lane];
      for (int hi = 0; hi < 16; hi++) {
        const int ring = hi & 3, blk = k2_block(hi + 4, pg);
        int it = 0;
        while (!((ready >> blk) & 1)) {
          uint32_t v;
          asm volatile("ld.relaxed.gpu.global.u32 %0, [%1];" : "=r"(v) : "l"(fp) : "memory");
          ready = __ballot_sync(0xffffffffu, v == epoch);
          if (++it > 4000000) asm volatile("trap;");
        }
        if (it) asm volatile("fence.proxy.async.global;" ::: "memory");
        if (hi >= 4) mbar_wait(sb + A_HE + 8 * ring, ((hi >> 2) - 1) & 1);
        if (lane == 0) {
          const uint32_t bar = sb + A_HF + 8 * ring;
          mbar_expect(bar, SLOT);
          bulk_g2s(sb + hslot(ring), (const uint8_t*)g_H + (size_t)(tt * 20 + blk) * SLOT, SLOT, bar);
        }
        __syncwarp();
      }
    } else {
      const int w = warp - 10;
      if (w == 0 && lane == 0) {
        const uint32_t tk = atomicAdd(&g_ticket, 1u);
        sts32(sb + A_EPV, tk / (NA + NB) + 1);
        mbar_arrive(sb + A_TKB);
        prefetch_tmap(&P.cre); prefetch_tmap(&P.cim); prefetch_tmap(&P.oa);
      }
      __syncwarp();
      sts32(sb + A_DSK + (w * 32 + lane) * 4, __ldg((const uint32_t*)P.dskip + pg * 64 + w * 32 + lane));
      cf L128[2];
#pragma unroll
      for (int z = 0; z < 2; z++) {
        const int pl = w * 64 + 2 * lane + z, p = pg * 128 + pl;
        const float lr = bf2f(P.lre + p), li = bf2f(P.lim + p);
        const float dt = __bfloat162float(__float2bfloat16_rn(expf(bf2f(P.logdt + p))));
        const float e = expf(dt * lr);
        float sn, cs; sincosf(dt * li, &sn, &cs);
        cf L; L.r = e * cs; L.i = e * sn;
        const float nr = L.r - 1.0f, den = 2.0f / (lr * lr + li * li);
        sts128f(sb + A_TAB + pl * 16, L.r, L.i, (nr * lr + L.i * li) * den, (L.i * lr - nr * li) * den);
#pragma unroll
        for (int i = 0; i < 7; i++) L = cmul(L, L);
        L128[z] = L;
      }
      cluster_wait();
      mbar_wait(sb + A_TKB, 0);
      const uint32_t epoch = lds32(sb + A_EPV);
      unsigned long long* ep = &g_E[pg * 128 + w * 64 + 2 * lane];
      unsigned int* fp = &g_flag[tt * 32 + pg * 4 + w * 2];
      if (tt < 15) {
        const uint32_t pe = epoch - 1;
        const unsigned long long v = ((unsigned long long)((pe >> 4) & 15u) << 32) | (pe & 15u);
        asm volatile("st.relaxed.gpu.global.v2.u64 [%0], {%1, %1};" ::"l"(ep + tt * 640), "l"(v) : "memory");
      }
      if (lane == 0) asm volatile("st.relaxed.gpu.global.v2.u32 [%0], {%1, %1};" ::"l"(fp), "r"(epoch - 1) : "memory");
      mbar_arrive(sb + A_EPB);
      mbar_wait(sb + A_G1D, 0);
      {
        const unsigned long long want = ((unsigned long long)((epoch >> 4) & 15u) << 32) | (epoch & 15u), tmask = 0x0000000f0000000full;
        unsigned long long e0[15], e1[15];
#pragma unroll
        for (int c = 0; c < 15; c++) { e0[c] = c < tt ? ~want : want; e1[c] = want; }
        int it = 0;
        bool ok;
        do {
          unsigned long long bad = 0;
#pragma unroll
          for (int c = 0; c < 15; c++) {
            if (((e0[c] ^ want) | (e1[c] ^ want)) & tmask)
              asm volatile("ld.relaxed.gpu.global.v2.u64 {%0, %1}, [%2];" : "=l"(e0[c]), "=l"(e1[c]) : "l"(ep + c * 640) : "memory");
          }
#pragma unroll
          for (int c = 0; c < 15; c++) bad |= (e0[c] ^ want) | (e1[c] ^ want);
          ok = __all_sync(0xffffffffu, (bad & tmask) == 0);
          if (++it > 2000000) asm volatile("trap;");
        } while (!ok);
        cf s0, s1; s0.r = s0.i = s1.r = s1.i = 0.f;
#pragma unroll
        for (int c = 0; c < 15; c++) {
          if (c < tt) {
            cf b; b.r = __uint_as_float((uint32_t)e0[c]); b.i = __uint_as_float((uint32_t)(e0[c] >> 32));
            s0 = cfma(L128[0], s0, b);
            b.r = __uint_as_float((uint32_t)e1[c]); b.i = __uint_as_float((uint32_t)(e1[c] >> 32));
            s1 = cfma(L128[1], s1, b);
          }
        }
        sts128f(sb + A_TAB + (w * 32 + lane) * 16, s0.r, s0.i, s1.r, s1.i);
        mbar_arrive(sb + A_SB + 8 * w);
      }
      uint8_t* gh = (uint8_t*)g_H + (size_t)(tt * 20 + pg * 4 + w * 2) * SLOT;
      if (w == 0) {
        mbar_wait(sb + A_HS, 0);
        if (lane == 0) {
          bulk_s2g(gh, sb + 1 * SLOT, 8192);
          bulk_s2g(gh + 16384, sb + 4 * SLOT, 8192);
        }
        __syncwarp();
        mbar_wait(sb + A_HS + 8, 0);
      } else {
        mbar_wait(sb + A_HS + 24, 0);
        mbar_wait(sb + A_PO, 0);
      }
      if (lane == 0) {
        if (w == 1) {
          bulk_s2g(gh, sb + 1 * SLOT + 8192, 8192);
          asm volatile("cp.async.bulk.commit_group;" ::: "memory");
          asm volatile("cp.async.bulk.wait_group 0;" ::: "memory");
        }
        bulk_s2g(gh + 8192, sb + 2 * SLOT + w * 8192, 8192);
        asm volatile("cp.async.bulk.commit_group;" ::: "memory");
        if (w == 0) {
          bulk_s2g(gh + 24576, sb + 5 * SLOT, 8192);
          asm volatile("cp.async.bulk.commit_group;" ::: "memory");
          asm volatile("cp.async.bulk.wait_group 1;" ::: "memory");
        } else {
          asm volatile("cp.async.bulk.wait_group 0;" ::: "memory");
        }
        asm volatile("st.relaxed.gpu.global.u32 [%0], %1;" ::"l"(fp), "r"(epoch) : "memory");
        if (w == 1) {
          bulk_s2g(gh + 16384, sb + 4 * SLOT + 8192, 8192);
          asm volatile("cp.async.bulk.commit_group;" ::: "memory");
          asm volatile("cp.async.bulk.wait_group 0;" ::: "memory");
        }
        if (w == 1) {
          bulk_s2g(gh + 24576, sb + 5 * SLOT + w * 8192, 8192);
          asm volatile("cp.async.bulk.commit_group;" ::: "memory");
        }
        asm volatile("cp.async.bulk.wait_group 0;" ::: "memory");
        asm volatile("st.relaxed.gpu.global.u32 [%0], %1;" ::"l"(fp + 1), "r"(epoch) : "memory");
        if (w == 0) mbar_arrive(sb + A_PO);
        mbar_arrive(sb + A_HD);
      }
    }
  }
}

__device__ __forceinline__ void roleA_cons(const Params& P, uint32_t sb, int cta) {
  const int tid = threadIdx.x, warp = __shfl_sync(0xffffffffu, tid >> 5, 0), lane = tid & 31;
  const int pg = cta >> 4, tt = cta & 15, rank = cta & 1;
  {
    cluster_arrive_relaxed();
    asm volatile("setmaxnreg.inc.sync.aligned.u32 208;");
    bar_sync(0, 384);
    const int w = warp >> 2, wq = warp & 3, r = lane >> 2, q = lane & 3;
    const bool leader = (tid & 127) == 0;
    const uint32_t peer_ce = mapa(sb + A_CE, rank ^ 1);
    const uint32_t d0 = mkdesc(sb, 16), dw = d0 + w * 512;
    const bool first4 = (tid & 127) < 4;
    cluster_wait();
    float are[64], aim[64];
#pragma unroll 1
    for (int kb = 0; kb < 10; kb++) {
      const int s = kb & 3;
      mbar_wait(sb + A_G1F + 8 * s, (kb >> 2) & 1);
      const uint32_t so = s * (3 * SLOT >> 4);
      wg_fence();
#pragma unroll
      for (int k = 0; k < 4; k++) {
        WSS<128, 0, 0, 1, 1>::run(are, dw + so + (SLOT >> 4) + 2 * k, d0 + so + 2 * k, (kb | k) != 0);
        WSS<128, 0, 0, 1, 1>::run(aim, dw + so + (2 * SLOT >> 4) + 2 * k, d0 + so + 2 * k, (kb | k) != 0);
      }
      wg_commit();
      wg_wait<1>();
      mbar_arrive_p(sb + A_G1E + 8 * ((kb - 1) & 3), leader && kb > 0 && kb < 7);
      mbar_arrive_p(sb + A_CE + 8 * (lane & 3), first4 && kb == ((lane & 3) == 3 ? 8 : 7));
      mbar_arrive_cluster_p(peer_ce + 8 * (lane & 3), first4 && kb == ((lane & 3) == 3 ? 8 : 7));
    }
    mbar_wait(sb + A_EPB, 0);
    const uint32_t epoch = lds32(sb + A_EPV);
    cf lam[2], c2[2], L32[2];
#pragma unroll
    for (int z = 0; z < 2; z++) {
      const uint4 t = lds128(sb + A_TAB + (w * 64 + wq * 16 + r + 8 * z) * 16);
      lam[z].r = __uint_as_float(t.x); lam[z].i = __uint_as_float(t.y); c2[z].r = __uint_as_float(t.z); c2[z].i = __uint_as_float(t.w);
      cf L = lam[z];
#pragma unroll
      for (int i = 0; i < 5; i++) L = cmul(L, L);
      L32[z] = L;
      asm volatile("" : "+f"(L32[z].r), "+f"(L32[z].i));
    }
    wg_wait<0>();
    fence_regs<64>(are); fence_regs<64>(aim);
    mbar_arrive(sb + A_G1D);

#pragma unroll
    for (int u = 1; u < 32; u++) {
#pragma unroll
      for (int z = 0; z < 2; z++) {
        const int idx = 4 * (u >> 1) + 2 * z + (u & 1), pdx = 4 * ((u - 1) >> 1) + 2 * z + ((u - 1) & 1);
        const float gr = fmaf(lam[z].r, are[pdx], fmaf(-lam[z].i, aim[pdx], are[idx]));
        const float gi = fmaf(lam[z].r, aim[pdx], fmaf(lam[z].i, are[pdx], aim[idx]));
        are[idx] = gr; aim[idx] = gi;
      }
    }
    const uint32_t tag_r = epoch & 15u, tag_i = (epoch >> 4) & 15u;
    cf init[2], Lq[2];
    unsigned long long* ep = &g_E[pg * 128 + w * 64 + wq * 16 + r];
#pragma unroll
    for (int z = 0; z < 2; z++) {
      cf e; e.r = are[61 + 2 * z]; e.i = aim[61 + 2 * z];
      cf v = cshfl_up(e, 1); if (q >= 1) e = cfma(L32[z], v, e);
      const cf L64 = cmul(L32[z], L32[z]);
      v = cshfl_up(e, 2); if (q >= 2) e = cfma(L64, v, e);
      if (q == 3 && tt < 15) {
        const uint32_t a = (__float_as_uint(e.r) & ~15u) | tag_r, b = (__float_as_uint(e.i) & ~15u) | tag_i;
        asm volatile("st.relaxed.gpu.global.u64 [%0], %1;" ::"l"(ep + tt * 640 + 8 * z), "l"(((unsigned long long)b << 32) | a) : "memory");
      }
      v = cshfl_up(e, 1); if (q == 0) { v.r = 0.f; v.i = 0.f; }
      init[z] = v;
      Lq[z].r = 1.f; Lq[z].i = 0.f;
      if (q & 1) Lq[z] = L32[z];
      if (q & 2) Lq[z] = cmul(Lq[z], L64);
    }
#pragma unroll
    for (int idx = 0; idx < 64; idx++) {
      const int z = (idx >> 1) & 1;
      const float gr = are[idx], gi = aim[idx];
      are[idx] = fmaf(c2[z].r, gr, -c2[z].i * gi);
      aim[idx] = fmaf(-c2[z].r, gi, -c2[z].i * gr);
    }
    fence_regs<64>(are); fence_regs<64>(aim);
    const uint32_t mrow = wq * 16 + (lane & 7) + 8 * ((lane >> 3) & 1);
    const uint32_t sw = lane & 7, hi = lane >> 4;
    uint32_t xs[32];
    {
      mbar_wait(sb + A_XF, 0);
      const uint32_t xbase = sb + 12 * SLOT + (w * 64 + mrow) * 128;
#pragma unroll
      for (int jp = 0; jp < 8; jp++) {
        uint32_t xr[4];
        ldsm4(xbase + (jp >> 2) * SLOT + (((((2 * jp) & 7) + hi) ^ sw) << 4), xr);
#pragma unroll
        for (int jj = 0; jj < 2; jj++) {
          const uint32_t dk = lds32(sb + A_DSK + (4 * (2 * jp + jj) + q) * 4);
          xs[4 * jp + 2 * jj] = bmul2(xr[2 * jj], dk); xs[4 * jp + 2 * jj + 1] = bmul2(xr[2 * jj + 1], dk);
          asm volatile("" : "+r"(xs[4 * jp + 2 * jj]), "+r"(xs[4 * jp + 2 * jj + 1]));
        }
      }
    }
    cf wv[2];
    {
      mbar_wait(sb + A_SB + 8 * w, 0);
#pragma unroll
      for (int z = 0; z < 2; z++) {
        const float2 t = lds64f(sb + A_TAB + (w * 64 + wq * 16 + r + 8 * z) * 8);
        cf S; S.r = t.x; S.i = t.y;
        wv[z] = cmul(c2[z], cfma(Lq[z], S, init[z]));
        wv[z].i = -wv[z].i;
      }
    }
    {
      const uint32_t rbase = sb + w * 8192 + mrow * 128;
#pragma unroll
      for (int jp = 0; jp < 8; jp++) {
        uint32_t pr[4], pi[4];
#pragma unroll
        for (int jj = 0; jj < 2; jj++) {
#pragma unroll
          for (int z = 0; z < 2; z++) {
            const int idx = 4 * (2 * jp + jj) + 2 * z;
            cf w0, w1;
            w0.r = fmaf(lam[z].r, wv[z].r, lam[z].i * wv[z].i); w0.i = fmaf(lam[z].r, wv[z].i, -lam[z].i * wv[z].r);
            w1.r = fmaf(lam[z].r, w0.r, lam[z].i * w0.i); w1.i = fmaf(lam[z].r, w0.i, -lam[z].i * w0.r);
            wv[z] = w1;
            pr[2 * jj + z] = pack_bf16(are[idx] + w0.r, are[idx + 1] + w1.r);
            pi[2 * jj + z] = pack_bf16(aim[idx] + w0.i, aim[idx + 1] + w1.i);
          }
        }
        const uint32_t chunk = ((2 * jp) & 7) + hi;
        const uint32_t off = rbase + ((chunk ^ sw) << 4) + (jp >= 4 ? SLOT : 0);
        stsm4(off + 1 * SLOT, pr[0], pr[1], pr[2], pr[3]);
        stsm4(off + 4 * SLOT, pi[0], pi[1], pi[2], pi[3]);
        if ((jp & 3) == 3) { fence_async_smem(); mbar_arrive(sb + A_HS + 16 * w + 8 * (jp >> 2)); }
      }
    }
    float acc[64];
#pragma unroll
    for (int j = 0; j < 32; j++) { acc[2 * j] = bf_lo(xs[j]); acc[2 * j + 1] = bf_hi(xs[j]); }
    fence_regs<64>(acc);
#pragma unroll 1
    for (int ci = 0; ci < 20; ci++) {
      const int ring = ci & 3;
      uint32_t dA;
      if (ci < 4) { mbar_wait(sb + A_HS + 16 * (ci >> 1) + 8 * w, 0); dA = d0 + w * 1024 + (((1 + 3 * (ci & 1)) * SLOT) >> 4) + (ci >> 1) * 512; }
      else { mbar_wait(sb + A_HF + 8 * ring, ((ci >> 2) - 1) & 1); dA = dw + (hslot(ring) >> 4); }
      mbar_wait(sb + A_CF + 8 * ring, (ci >> 2) & 1);
      const uint32_t dB = d0 + (cslot(ring) >> 4);
      wg_fence();
#pragma unroll
      for (int k = 0; k < 4; k++) WSS<128, 1, 0, 1, 1>::run(acc, dA + k * 128, dB + 2 * k, 1);
      wg_commit();
      wg_wait<1>();
      mbar_arrive_p(sb + A_CE + 8 * ((ci - 1) & 3), leader && ci > 0 && ci <= 16);
      mbar_arrive_cluster_p(peer_ce + 8 * ((ci - 1) & 3), leader && ci > 0 && ci <= 16);
      mbar_arrive_p(sb + A_HE + 8 * ((ci - 1) & 3), leader && ci > 4);
    }
    wg_wait<0>();
    fence_regs<64>(acc);
    {
      mbar_wait(sb + A_HD, 0);
      const uint32_t ob = sb + (1 + 3 * w) * SLOT + (wq * 16 + r) * 128 + (q & 1) * 8;
      const bool odd = r & 1;
#pragma unroll
      for (int bx = 0; bx < 4; bx++) {
#pragma unroll
        for (int jj = 0; jj < 4; jj++) {
          const int i0 = 4 * (4 * bx + jj), i1 = 4 * (4 * bx + (jj ^ 2));
          const uint32_t ch = (uint32_t)(((odd ? (jj ^ 2) : jj) * 2 + (q >> 1)) ^ r) << 4;
          sts64f(ob + bx * 8192 + ch, odd ? acc[i1] : acc[i0], odd ? acc[i1 + 1] : acc[i0 + 1]);
          sts64f(ob + bx * 8192 + 1024 + ch, odd ? acc[i1 + 2] : acc[i0 + 2], odd ? acc[i1 + 3] : acc[i0 + 3]);
        }
        if (bx & 1) {
          fence_async_smem();
          bar_sync(1 + w, 128);
          if (leader) {
            tma5d_store(&P.oa, sb + (1 + 3 * w) * SLOT + (bx - 1) * 8192, pg * 128 + 32 * (bx - 1), 8 * w, tt);
            tma5d_store(&P.oa, sb + (1 + 3 * w) * SLOT + bx * 8192, pg * 128 + 32 * bx, 8 * w, tt);
          }
        }
      }
      if (leader) {
        asm volatile("cp.async.bulk.commit_group;" ::: "memory");
        asm volatile("cp.async.bulk.wait_group.read 0;" ::: "memory");
      }
    }
  }
}

constexpr uint32_t B_U = 0, B_STRIP = 132 * 16, B_CH = 265 * 16, B_USZ = 16 * B_CH;
__host__ __device__ constexpr uint32_t chbase(int c) { return (uint32_t)c * B_CH; }
constexpr uint32_t B_KC = B_USZ, KC_C1 = 1048 * 4, KC_BUF = 2096 * 4;
constexpr uint32_t B_X = B_KC + 4 * KC_BUF, X_Z = 136 * 16, X_CLS = 2 * X_Z, X_BUF = 4 * X_CLS;
constexpr uint32_t B_OST = B_X + 2 * X_BUF;
constexpr uint32_t B_Q1 = B_OST + 16384, B_Q0 = B_Q1 + 32768;
constexpr uint32_t ST_K = 33 * 512, ST_CH = ST_K + 32 * 512, B_ST = (B_KC + 2 * KC_BUF + 511) / 512 * 512;
constexpr uint32_t B_BAR = B_ST + 4 * ST_CH;
constexpr uint32_t B_KST = B_BAR  , B_KSE = B_BAR + 64  , B_KF = B_BAR + 96, B_KE = B_BAR + 128, B_KR = B_BAR + 160, B_PF = B_BAR + 192,
                   B_QF = B_BAR + 200  , B_GD = B_BAR + 216, B_ZR = B_BAR + 224  , B_ZG = B_BAR + 232  , B_SHK = B_BAR + 240  , B_SSD = B_BAR + 496  ,
                   B_TAB = B_BAR + 576  , B_EPV = B_BAR + 640, B_UR = B_BAR + 648  ;
static_assert(B_X % 128 == 0 && B_OST % 128 == 0 && B_KC % 128 == 0 && B_Q1 % 256 == 0 && B_KC + 65536 <= B_OST, "align");
static_assert(B_Q0 + 32768 <= B_BAR && B_BAR + 704 <= SMEM_BYTES, "smem");

struct BGeom {
  int W0;
  bool wide;
  int t;
  int npos, blk;
  int nside, octO, octS, jq;
  uint32_t order;
  __device__ __forceinline__ BGeom(int cta) {
    const int g = cta / 10, idx = cta - 10 * g;
    t = (int)((0x1032443210ull >> (4 * idx)) & 15);
    W0 = 128 * g + (idx >= 5 ? 64 : 0) + (int)((0x32110u >> (4 * t)) & 15) * 16;
    nside = t == 2 ? 6 : t == 4 ? 4 : 5;
    npos = t == 4 ? 12 : 13;
    blk = 2 * g + (idx >= 5 ? 1 : 0);
    octO = (0x11200u >> (4 * t)) & 15; octS = (0x02111u >> (4 * t)) & 15;
    jq = (t == 2 || t == 4) ? 4 : 0;
    wide = (t == 2 || t == 3);
    order = t == 0 ? 0x43210u : t == 1 ? 0x65410u : t == 2 ? 0x765432u : t == 3 ? 0x34210u : 0x7654u;
  }
  __device__ __forceinline__ int slot(int i) const { return i < nside ? (int)((order >> (4 * i)) & 15u) : 8 + i - nside; }
  __device__ __forceinline__ int wch(int sl) const {
    if (sl >= 8) return 8 * octO + sl - 8;
    if (t == 1 && sl >= 4) return sl - 7;
    if (t == 3 && sl == 4) return 7;
    return 8 * octS + sl;
  }
};

__host__ __device__ constexpr int conv_order(int s) { return (s & 1) ? 15 - (s >> 1) : (s >> 1); }
template <int S> __device__ __forceinline__ void conv_lds(uint32_t* f, uint32_t kaddr) {
  const uint32_t a = kaddr + 256 * conv_order(S);
  f[8 * S + 1] = lds32(a); f[8 * S + 0] = lds32(a + 16); f[8 * S + 2] = lds32(a + 32); f[8 * S + 4] = lds32(a + 48); f[8 * S + 6] = lds32(a + 64);
}
template <int S> __device__ __forceinline__ void conv_dup(uint32_t* f, uint32_t zero) {
  asm volatile("xor.b32 %0, %1, %2;" : "=r"(f[8 * S + 3]) : "r"(f[8 * S + 0]), "r"(zero));
  asm volatile("xor.b32 %0, %1, %2;" : "=r"(f[8 * S + 5]) : "r"(f[8 * S + 2]), "r"(zero));
  asm volatile("xor.b32 %0, %1, %2;" : "=r"(f[8 * S + 7]) : "r"(f[8 * S + 4]), "r"(zero));
}
template <int S> __device__ __forceinline__ void conv_mma(float* acc, const uint32_t* f, uint64_t ud) {
  constexpr int M = conv_order(S);
  WRS<128 - 8 * M>::run(acc, f[8 * S], f[8 * S + 1], f[8 * S + 2], f[8 * S + 3], ud + 8 * M, M != 0);
  WRS<128 - 8 * M>::run(acc, f[8 * S + 4], f[8 * S + 5], f[8 * S + 6], f[8 * S + 7], ud + 8 * M + 1, 1);
}
template <int S0, int S1> struct ConvRange {
  static __device__ __forceinline__ void lds(uint32_t* f, uint32_t ka) { conv_lds<S0>(f, ka); ConvRange<S0 + 1, S1>::lds(f, ka); }
  static __device__ __forceinline__ void dup(uint32_t* f, uint32_t z) { conv_dup<S0>(f, z); ConvRange<S0 + 1, S1>::dup(f, z); }
  static __device__ __forceinline__ void mma(float* acc, const uint32_t* f, uint64_t ud) { conv_mma<S0>(acc, f, ud); ConvRange<S0 + 1, S1>::mma(acc, f, ud); }
};
template <int S1> struct ConvRange<S1, S1> {
  static __device__ __forceinline__ void lds(uint32_t*, uint32_t) {}
  static __device__ __forceinline__ void dup(uint32_t*, uint32_t) {}
  static __device__ __forceinline__ void mma(float*, const uint32_t*, uint64_t) {}
};
template <int J> __device__ __forceinline__ void dump_step(const float* acc, uint32_t xw) {
  stsm4t(xw + J * 256, pack_bf16(acc[8 * J], acc[8 * J + 1]), pack_bf16(acc[8 * J + 2], acc[8 * J + 3]),
         pack_bf16(acc[8 * J + 4], acc[8 * J + 5]), pack_bf16(acc[8 * J + 6], acc[8 * J + 7]));
}

__device__ __forceinline__ uint32_t q_addr(uint32_t sb, const BGeom& G, bool side, int lane, uint32_t& stride) {
  const int row = 8 * (lane >> 3) + 7 - (lane & 7);
  stride = G.wide ? 512 : 1024;
  if (G.wide) return sb + (side ? B_Q1 : B_Q0) + row * 16;
  return sb + B_Q1 + row * 32 + (((side ? G.octS : G.octO) ^ ((row >> 2) & 1)) << 4);
}
__device__ __forceinline__ void final_tile(uint32_t za, uint32_t qa, uint32_t qs, uint32_t st, int tb) {
  uint32_t z[4], qq[4];
  ldsm4t(za - tb * 32, z);
  ldsm4(qa + tb * qs, qq);
#pragma unroll
  for (int m = 0; m < 4; m++) {
    const uint32_t o = bmul2(qq[m], z[m]);
    sts64f(st + m * 256, bf_lo(o), bf_hi(o));
  }
}
__device__ __forceinline__ void tma2d_store(const CUtensorMap* m, uint32_t src, int c0, int c1) {
  asm volatile("cp.async.bulk.tensor.2d.global.shared::cta.bulk_group [%0, {%2, %3}], [%1];" ::"l"(m), "r"(src), "r"(c0), "r"(c1) : "memory");
}
__device__ __forceinline__ void final_last(const Params& P, uint32_t sb, const BGeom& G, int warp, int lane) {
  const int col = DM + G.W0 + 8 * G.octO;
  const int mi = lane >> 3, mr = lane & 7, i = lane >> 2, q = lane & 3;
  const uint32_t za = sb + B_U + chbase(8 + mr) + (1 - (mi & 1)) * B_STRIP + (127 - (mi >> 1)) * 16;
  uint32_t qs;
  const uint32_t qa = q_addr(sb, G, false, lane, qs);
  const uint32_t st = sb + B_KC + (7 - i) * 32 + q * 8;
#pragma unroll 1
  for (int ck = warp >> 2; ck < 8; ck += 3) {
    const int tb = ck * 8 + (warp & 3) * 2;
    final_tile(za, qa, qs, st + tb * 1024, tb);
    final_tile(za, qa, qs, st + tb * 1024 + 1024, tb + 1);
    fence_async_smem();
    bar_sync(6 + (warp >> 2), 128);
    if ((warp & 3) == 0 && lane == 0) tma2d_store(&P.ob, sb + B_KC + ck * 8192, col, ck * 256);
  }
  if ((warp & 3) == 0 && lane == 0) {
    asm volatile("cp.async.bulk.commit_group;" ::: "memory");
    asm volatile("cp.async.bulk.wait_group.read 0;" ::: "memory");
  }
}
__device__ __forceinline__ void b_issue_chunk(const Params& P, uint32_t sb, int c, int W0, bool wide) {
  const uint32_t dst = sb + B_ST + (wide ? (c & 3) * ST_CH : c * (ST_CH / 2)), bar = sb + B_KST + 8 * c;
  mbar_expect(bar, wide ? ST_CH : ST_CH / 2);
  tma3d(dst, wide ? &P.k : &P.k16, W0, c * 32 - 1, 0, bar);
  tma3d(dst + (wide ? ST_K : ST_K / 2), wide ? &P.v : &P.v16, W0, c * 32, 0, bar);
}
__device__ __forceinline__ void b_issue_filter(const Params& P, uint32_t sb, int i, int gch) {
  mbar_expect(sb + B_KR + 8 * (i & 3), 4096);
  bulk_g2s(sb + B_KC + (i & 3) * KC_BUF + 32, P.ssmk + (size_t)gch * SEQ, 4096, sb + B_KR + 8 * (i & 3));
}

__device__ __forceinline__ void b_entry(const Params& P, uint32_t sb, int cta) {
  const BGeom G(cta);
  b_issue_chunk(P, sb, 0, G.W0, G.wide);
  const int nw = G.wide ? 32 : 16, pre = G.t == 1 ? 8 : 0;
  mbar_expect(sb + B_PF, nw * 10 + pre * 2);
  bulk_g2s(sb + B_SHK, P.shk + G.W0 * 4, nw * 8, sb + B_PF);
  bulk_g2s(sb + B_SSD + 16 - pre * 2, P.ssmd + G.W0 - pre, (nw + pre) * 2, sb + B_PF);
#pragma unroll 1
  for (int i = 1; i < (G.wide ? 4 : 8); i++) {
    b_issue_chunk(P, sb, i, G.W0, G.wide);
    if (i < 3) b_issue_filter(P, sb, i - 1, G.W0 + G.wch(G.slot(i - 1)));
  }
}

__device__ __forceinline__ void roleB_serv(const Params& P, uint32_t sb, int cta) {
  const int tid = threadIdx.x, warp = __shfl_sync(0xffffffffu, tid >> 5, 0), lane = tid & 31;
  asm volatile("setmaxnreg.dec.sync.aligned.u32 56;");
  const BGeom G(cta);
  const int nch = G.npos;
  if (warp == 8) {
    cluster_arrive_relaxed();
    bar_sync(9, 128);
    if (G.wide) {
#pragma unroll 1
      for (int i = 4; i < 8; i++) {
        mbar_wait_bg(sb + B_KSE + 8 * (i - 4), 0);
        if (lane == 0) b_issue_chunk(P, sb, i, G.W0, true);
        __syncwarp();
      }
    }
    if (lane >= 2 && lane < nch)
      asm volatile("cp.async.bulk.prefetch.L2.global [%0], %1;" ::"l"(P.ssmk + (size_t)(G.W0 + G.wch(G.slot(lane))) * SEQ), "r"(4096) : "memory");
    if (lane == 0) { prefetch_tmap(G.wide ? &P.q : &P.q16); prefetch_tmap(&P.ob); prefetch_tmap(G.t ? &P.o4 : &P.oh); }
    __syncwarp();
    cluster_wait();
    bar_sync(3, 384);
    if (lane == 0) {
      if (G.t == 0 || G.t == 2) {
        const uint32_t dst = mapa(sb + B_U + chbase(4), 1), bar = mapa(sb + B_UR, 1);
        asm volatile("cp.async.bulk.shared::cluster.shared::cta.mbarrier::complete_tx::bytes [%0], [%1], %2, [%3];" ::"r"(dst),
                     "r"(sb + B_U + chbase(G.t ? 15 : 5)), "r"(G.t ? B_CH - 16 : 3 * B_CH - 16), "r"(bar) : "memory");
      }
      b_issue_filter(P, sb, 2, G.W0 + G.wch(G.slot(2))); b_issue_filter(P, sb, 3, G.W0 + G.wch(G.slot(3)));
    }
#pragma unroll 1
    for (int i = 4; i < 12 || i < nch; i++) {
      if (i < nch) mbar_wait_bg(sb + B_KE + 8 * (i & 3), ((i >> 2) - 1) & 1);
      if (lane == 0) {
        if (i < nch) b_issue_filter(P, sb, i, G.W0 + G.wch(G.slot(i)));
        if (i < 12) {
          if (G.wide) {
            const int r0 = (i & 3) * 512;
            const uint32_t dst = sb + (i < 8 ? B_Q1 : B_Q0) + r0 * 16, bar = sb + B_QF + (i < 8 ? 8 : 0);
            const int col = G.W0 + 8 * (i < 8 ? G.octS : G.octO);
            tma2d(dst, &P.q, col, r0, bar);
            tma2d(dst + 4096, &P.q, col, r0 + 256, bar);
          } else if (i < 8) {
            const int r0 = (i & 3) * 512;
            tma2d(sb + B_Q1 + r0 * 32, &P.q16, G.W0, r0, sb + B_QF + 8);
            tma2d(sb + B_Q1 + r0 * 32 + 8192, &P.q16, G.W0, r0 + 256, sb + B_QF + 8);
          }
        }
      }
      __syncwarp();
    }
  } else if (warp == 9) {
    if (lane < 8) {
      const int b = lane >> 2, part = lane & 3;
      sts128(sb + B_KC + b * KC_BUF + (part >> 1) * KC_C1 + (part & 1) * 16, 0, 0, 0, 0);
    }
    __syncwarp();
    cluster_arrive_relaxed();
    bar_sync(0, 384);
    bar_sync(9, 128);
#pragma unroll 1
    for (int i = 0; i < nch; i++) {
      const int kb = i & 3;
      const uint32_t src = sb + B_KC + kb * KC_BUF + 32;
      mbar_wait_bg(sb + B_KR + 8 * kb, (i >> 2) & 1);
#pragma unroll
      for (int h = 0; h < 8; h++) {
        const int x = lane + 32 * h;
        const uint4 kk = lds128(src + x * 16);
        const uint32_t nx = (x < 255) ? lds32(src + x * 16 + 16) : 0u;
        sts128(src + KC_C1 + x * 16, __byte_perm(kk.x, kk.y, 0x5432), __byte_perm(kk.y, kk.z, 0x5432), __byte_perm(kk.z, kk.w, 0x5432),
               __byte_perm(kk.w, nx, 0x5432));
        if (x == 0) sts32(src + KC_C1 - 4, kk.x << 16);
      }
      mbar_arrive(sb + B_KF + 8 * kb);
      if (i == 1) {
        cluster_wait();
        bar_sync(3, 384);
        if (lane < 8) {
          const int b = 2 + (lane >> 2), part = lane & 3;
          sts128(sb + B_KC + b * KC_BUF + (part >> 1) * KC_C1 + (part & 1) * 16, 0, 0, 0, 0);
        }
        __syncwarp();
      }
    }
  } else {
    if (warp == 10) {
      if (lane == 0) {
        for (int i = 0; i < 4; i++) { mbar_init(sb + B_KSE + 8 * i, 2); mbar_init(sb + B_KF + 8 * i, 32); mbar_init(sb + B_KE + 8 * i, 4); }
        mbar_init(sb + B_QF, 1); mbar_init(sb + B_QF + 8, 1); mbar_init(sb + B_GD, 4 * G.nside); mbar_init(sb + B_ZR, 1);
        mbar_init(sb + B_ZG, G.t == 2 ? 2 : 1); mbar_init(sb + B_UR, 1);
        asm volatile("fence.mbarrier_init.release.cluster;" ::: "memory");
        if (G.wide) { mbar_expect(sb + B_QF, 32768); mbar_expect(sb + B_QF + 8, 32768); } else mbar_expect(sb + B_QF + 8, 65536);
        mbar_expect(sb + B_ZR, G.t == 0 ? 3 * (B_CH - 16) : B_CH - 16);
        mbar_expect(sb + B_UR, G.t == 1 ? 3 * B_CH - 16 : G.t == 3 ? B_CH - 16 : 0);
      }
    } else {
      sts128(sb + B_U + chbase(lane >> 1) + (lane & 1) * B_STRIP + 128 * 16, 0, 0, 0, 0);
      fence_async_smem();
    }
    __syncwarp();
    cluster_arrive_relaxed();
    bar_sync(0, 384);
    bar_sync(9, 128);
    if (warp == 11) {
      if (lane == 0) {
        const uint32_t ep = atomicAdd(&g_ticket, 1u) / (NA + NB) + 1;
        sts32(sb + B_EPV, ep);
        if (G.t == 2) asm volatile("st.relaxed.gpu.global.u32 [%0], %1;" ::"l"(&g_zflag[G.blk * 32]), "r"(ep - 1) : "memory");
      }
      __syncwarp();
      mbar_wait_bg(sb + B_PF, 0);
      if (lane < 16) {
        const int sl = G.slot(lane < nch ? lane : 0), wc = G.wch(sl);
        sts32(sb + B_TAB + lane * 4, __byte_perm(lds32(sb + B_SSD + 16 + (wc >> 1) * 4), 0, (wc & 1) ? 0x3232 : 0x1010));
      }
      __syncwarp();
    }
    cluster_wait();
    bar_sync(3, 384);
    const int mi = lane >> 3, mr = lane & 7, q = lane & 3;
    const uint32_t za = sb + B_U + chbase(mr) + (1 - (mi & 1)) * B_STRIP + (127 - (mi >> 1)) * 16;
    uint32_t qs;
    const uint32_t qa = q_addr(sb, G, true, lane, qs);
    const bool st = G.t != 0;
    const uint32_t so = st ? (7 - (lane >> 2)) * 16 + (q & 1) * 8 : (7 - (lane >> 2)) * 32 + q * 8;
    const bool on = !st || ((q >> 1) == (G.jq >> 2));
    if (G.t == 2 && warp == 11) {
      mbar_wait_bg(sb + B_ZG, 0);
      if (lane == 0) {
        bulk_s2g((uint8_t*)g_Z + (size_t)G.blk * 2 * B_CH, sb + B_U + chbase(2), 2 * B_CH - 16);
        asm volatile("cp.async.bulk.commit_group;" ::: "memory");
        asm volatile("cp.async.bulk.wait_group 0;" ::: "memory");
        asm volatile("st.relaxed.gpu.global.u32 [%0], %1;" ::"l"(&g_zflag[G.blk * 32]), "r"(lds32(sb + B_EPV)) : "memory");
      }
      __syncwarp();
    }
    mbar_wait_bg(sb + B_GD, 0); mbar_wait_bg(sb + B_QF + 8, 0);
    if (G.t == 0) mbar_wait_bg(sb + B_ZR, 0);
    if (G.t == 1) {
      if (warp == 10) {
        const uint32_t ep = lds32(sb + B_EPV);
        uint32_t v; int it = 0;
        do {
          asm volatile("ld.relaxed.gpu.global.u32 %0, [%1];" : "=r"(v) : "l"(&g_zflag[G.blk * 32]) : "memory");
          if (++it > 4000000) asm volatile("trap;");
        } while (v != ep);
        asm volatile("fence.proxy.async.global;" ::: "memory");
        if (lane == 0) { mbar_expect(sb + B_ZG, 2 * B_CH - 16); bulk_g2s(sb + B_U + chbase(2), (const uint8_t*)g_Z + (size_t)G.blk * 2 * B_CH, 2 * B_CH - 16, sb + B_ZG); }
        __syncwarp();
      }
      mbar_wait_bg(sb + B_ZG, 0);
    }
#pragma unroll 1
    for (int ck = warp - 10; ck < 16; ck += 2) {
      const uint32_t ost = sb + B_OST + (ck & 3) * 4096;
      if (lane == 0) asm volatile("cp.async.bulk.wait_group.read 1;" ::: "memory");
      __syncwarp();
      {
        uint32_t z[16], qq[16];
#pragma unroll
        for (int u = 0; u < 4; u++) { ldsm4t(za - (ck * 4 + u) * 32, z + 4 * u); ldsm4(qa + (ck * 4 + u) * qs, qq + 4 * u); }
#pragma unroll
        for (int m = 0; m < 16; m++) {
          const uint32_t o = bmul2(qq[m], z[m]);
          if (on) sts64f(ost + so + m * (st ? 128 : 256), bf_lo(o), bf_hi(o));
        }
      }
      fence_async_smem();
      __syncwarp();
      if (lane == 0) {
        tma2d_store(st ? &P.o4 : &P.oh, ost, DM + G.W0 + 8 * G.octS + G.jq, ck * 128);
        asm volatile("cp.async.bulk.commit_group;" ::: "memory");
      }
    }
    if (lane == 0) asm volatile("cp.async.bulk.wait_group.read 0;" ::: "memory");
    __syncwarp();
  }
  bar_sync(0, 384);
  mbar_wait_bg(sb + B_QF + (G.wide ? 0 : 8), 0);
  if (G.t == 2) mbar_wait_bg(sb + B_ZR, 0);
  final_last(P, sb, G, warp, lane);
}

__device__ __forceinline__ void roleB_conv(const Params& P, uint32_t sb, int cta) {
  const int tid = threadIdx.x, warp = __shfl_sync(0xffffffffu, tid >> 5, 0), lane = tid & 31, wg = warp >> 2, t128 = tid & 127;
  const BGeom G(cta);
  int npos = G.npos, nside = G.nside, xm = G.t == 1 ? 0x1c : G.t == 3 ? 0x8 : G.t == 2 ? 0x3 : 0, xoff = G.t == 1 ? B_CH : G.t == 3 ? 11 * B_CH : 0;
  asm volatile("" : "+r"(npos), "+r"(nside), "+r"(xm), "+r"(xoff));
  npos = __shfl_sync(0xffffffffu, npos, 0); nside = __shfl_sync(0xffffffffu, nside, 0); xm = __shfl_sync(0xffffffffu, xm, 0);
  int nitw = (G.npos + 1 - wg) >> 1;
  asm volatile("" : "+r"(nitw));
  nitw = __shfl_sync(0xffffffffu, nitw, 0);
  uint32_t slots = 0;
#pragma unroll
  for (int j = 6; j >= 0; j--) slots = (slots << 4) | (uint32_t)G.slot(2 * j + wg);
  asm volatile("" : "+r"(slots));
  slots = __shfl_sync(0xffffffffu, slots, 0);
  cluster_arrive_relaxed();
  bar_sync(0, 384);
  {
    const uint32_t pitch = G.wide ? 64 : 32, swm = G.wide ? 0x30 : 0x10;
    mbar_wait(sb + B_PF, 0);
#pragma unroll 1
    for (int task = warp; task < 16; task += 8) {
      const int c = task >> 1, o = (task & 1) + (G.wide ? 1 : 0);
      int dl = 0, jlo = G.jq, jhi = G.jq + 4;
      if (o == G.octO) { dl = 8; jlo = 0; jhi = 8; }
      else if (G.t == 0) jhi = 8;
      else if (G.t == 1) jhi = 2;
      else if (G.t == 2) jlo = 2;
      uint32_t wt[4][4];
#pragma unroll
      for (int cp = 0; cp < 4; cp++) {
        const uint4 ww = lds128(sb + B_SHK + o * 64 + cp * 16);
        wt[0][cp] = __byte_perm(ww.x, ww.z, 0x5410); wt[1][cp] = __byte_perm(ww.x, ww.z, 0x7632);
        wt[2][cp] = __byte_perm(ww.y, ww.w, 0x5410); wt[3][cp] = __byte_perm(ww.y, ww.w, 0x7632);
      }
      mbar_wait(sb + B_KST + 8 * c, 0);
      uint32_t kr[11][4];
      const uint32_t ka = sb + B_ST + (G.wide ? (c & 3) * ST_CH : c * (ST_CH / 2)) + lane * pitch + o * 16;
#pragma unroll
      for (int i = 0; i < 11; i++) {
        const uint32_t a = ka + (i < 3 ? (5 + i) * 33 : 1 + (i - 3) * 33) * pitch;
        const uint4 t = lds128(a ^ ((a >> 3) & swm));
        kr[i][0] = t.x; kr[i][1] = t.y; kr[i][2] = t.z; kr[i][3] = t.w;
      }
      uint32_t kv[8][4];
#pragma unroll
      for (int i = 0; i < 8; i++) {
        const uint4 vt = lds128((ka ^ ((ka >> 3) & swm)) + (264 + i * 32) * pitch);
        const uint32_t vr[4] = {vt.x, vt.y, vt.z, vt.w};
#pragma unroll
        for (int cp = 0; cp < 4; cp++) {
          uint32_t a = bmul2(kr[i][cp], wt[3][cp]);
          a = badd2(a, bmul2(kr[i + 1][cp], wt[2][cp]));
          a = badd2(a, bmul2(kr[i + 2][cp], wt[1][cp]));
          a = badd2(a, bmul2(kr[i + 3][cp], wt[0][cp]));
          kv[i][cp] = bmul2(a, vr[cp]);
        }
      }
      __syncwarp();
      if (c < 4 && lane == 0) mbar_arrive(sb + B_KSE + 8 * c);
      const int kap = c * 32 + lane;
      const uint32_t ua = sb + B_U + dl * (int)B_CH + (1 - (kap & 1)) * B_STRIP + (127 - (kap >> 1)) * 16;
#pragma unroll
      for (int j = 0; j < 8; j++) {
        const uint32_t sel = (j & 1) ? 0x7632 : 0x5410;
        if (j >= jlo && j < jhi)
          sts128(ua + j * B_CH, __byte_perm(kv[7][j >> 1], kv[6][j >> 1], sel), __byte_perm(kv[5][j >> 1], kv[4][j >> 1], sel),
                 __byte_perm(kv[3][j >> 1], kv[2][j >> 1], sel), __byte_perm(kv[1][j >> 1], kv[0][j >> 1], sel));
      }
    }
    fence_async_smem();
  }
  asm volatile("setmaxnreg.inc.sync.aligned.u32 224;");
  const int wq = warp & 3, i = lane >> 2, q = lane & 3;
  const uint32_t xb = sb + B_X + wg * X_BUF;
  const uint32_t koff = ((i & 1) ? KC_C1 : 0) + (16 * wq + 4 + q - ((i + 1) >> 1)) * 4;
  const uint32_t xw = xb + wq * X_CLS + ((lane >> 3) & 1) * X_Z + (8 * (lane >> 4) + (lane & 7) + 6 - 2 * wq) * 16;
  const int zo = wq >> 1, jo = 8 * (wq & 1);
  const uint32_t xr = xb + zo * X_Z + (8 * jo + lane + 6) * 16;
  const uint32_t uo = zo * B_STRIP + (8 * jo + lane) * 16;
  if (wg == 1) bar_arrive(4, 256);
  uint32_t f[128];
  mbar_wait(sb + B_KF + 8 * wg, 0);
  ConvRange<0, 16>::lds(f, sb + B_KC + wg * KC_BUF + koff);
  ConvRange<0, 16>::dup(f, P.zero);
  __syncwarp();
  if (lane == 0) mbar_arrive(sb + B_KE + 8 * wg);
  cluster_wait();
  bar_sync(3, 384);
  if (t128 < 48) {
    const int cls = t128 >> 4, z = (t128 >> 3) & 1, k = t128 & 7;
    if (k < 2 * (cls + 1)) sts128(xb + (cls + 1) * X_CLS + z * X_Z + (133 - k) * 16, 0, 0, 0, 0);
  }
#pragma unroll 1
  for (int it = 0; it < nitw; it++) {
    const int pos = 2 * it + wg;
    const uint32_t ub = sb + B_U + ((slots >> (4 * it)) & 15u) * B_CH;
    float acc[64];
    {
      const uint64_t ud = (uint64_t)mkdesc(ub, B_STRIP) | (8ull << 32);
      if (it == 1) mbar_wait(sb + B_UR, 0);
      bar_sync(4 + wg, 256);
      wg_fence();
      ConvRange<0, 8>::mma(acc, f, ud);
      wg_commit();
      ConvRange<8, 14>::mma(acc, f, ud);
      if (pos + 1 < npos) bar_arrive(5 - wg, 256);
      ConvRange<14, 16>::mma(acc, f, ud);
      wg_commit();
    }
    const int kb = (pos + 2) & 3;
    const uint32_t d2 = lds32(sb + B_TAB + pos * 4);
    if (pos + 2 < npos) mbar_wait(sb + B_KF + 8 * kb, ((pos + 2) >> 2) & 1);
    const uint32_t ka = sb + B_KC + kb * KC_BUF + koff;
    wg_wait<1>();
    ConvRange<0, 8>::lds(f, ka); ConvRange<0, 6>::dup(f, P.zero);
    wg_wait<0>();
    fence_regs<64>(acc);
    dump_step<0>(acc, xw); dump_step<1>(acc, xw); conv_lds<8>(f, ka); dump_step<2>(acc, xw); dump_step<3>(acc, xw); conv_lds<9>(f, ka);
    dump_step<4>(acc, xw); dump_step<5>(acc, xw); conv_lds<10>(f, ka); dump_step<6>(acc, xw); dump_step<7>(acc, xw); conv_lds<11>(f, ka);
    bar_sync(1 + wg, 128);
    uint32_t zz[8];
#pragma unroll
    for (int h = 0; h < 2; h++) {
      uint32_t kvr[4], p0[4], p1[4], p2[4], p3[4];
      ldsm4t(xr + h * 512, p0); ldsm4t(xr + X_CLS + h * 512, p1); ldsm4t(xr + 2 * X_CLS + h * 512, p2); ldsm4t(xr + 3 * X_CLS + h * 512, p3);
      ldsm4t(ub + uo + h * 512, kvr);
      if (h == 0) ConvRange<12, 14>::lds(f, ka); else ConvRange<14, 16>::lds(f, ka);
#pragma unroll
      for (int j = 0; j < 4; j++) {
        const uint32_t y = pack_bf16((bf_lo(p0[j]) + bf_lo(p1[j])) + (bf_lo(p2[j]) + bf_lo(p3[j])),
                                     (bf_hi(p0[j]) + bf_hi(p1[j])) + (bf_hi(p2[j]) + bf_hi(p3[j])));
        zz[4 * h + j] = badd2(y, bmul2(kvr[j], d2));
      }
    }
    stsm4t(ub + uo, zz[0], zz[1], zz[2], zz[3]);
    stsm4t(ub + uo + 512, zz[4], zz[5], zz[6], zz[7]);
    ConvRange<6, 16>::dup(f, P.zero);
    if ((xm >> pos) & 1) {
      fence_async_smem();
      bar_sync(1 + wg, 128);
      if (t128 == 0) {
        if (xoff) {
          const uint32_t dst = mapa(ub + xoff, 0), bar = mapa(sb + B_ZR, 0);
          asm volatile("cp.async.bulk.shared::cluster.shared::cta.mbarrier::complete_tx::bytes [%0], [%1], %2, [%3];" ::"r"(dst), "r"(ub),
                       "r"(264 * 16), "r"(bar) : "memory");
        } else {
          mbar_arrive(sb + B_ZG);
        }
      }
    }
    __syncwarp();
    if (lane == 0) { if (pos + 2 < npos) mbar_arrive(sb + B_KE + 8 * kb); if (pos < nside) mbar_arrive(sb + B_GD); }
  }
  bar_sync(0, 384);
  mbar_wait(sb + B_QF + (G.wide ? 0 : 8), 0);
  if (G.t == 2) mbar_wait(sb + B_ZR, 0);
  final_last(P, sb, G, warp, lane);
}

__global__ void __cluster_dims__(2, 1, 1) __launch_bounds__(384, 1) fused_kernel(const __grid_constant__ Params P) {
  extern __shared__ __align__(1024) uint8_t smem[];
  uint32_t sb = smem_u32(smem);
  asm volatile("mov.b32 %0, %0;" : "+r"(sb));
  sb = __shfl_sync(0xffffffffu, sb, 0);
  if (sb & 1023u) asm volatile("trap;");
  const int b = blockIdx.x;
  if ((threadIdx.x >> 5) == 8) {
    if (threadIdx.x == 256) {
      const uint32_t fb = sb + (b < NA ? A_G1F : B_KST);
      for (int i = 0; i < 4; i++) mbar_init(fb + 8 * i, 1);
      if (b >= NA) {
        for (int i = 4; i < 8; i++) mbar_init(fb + 8 * i, 1);
        for (int i = 0; i < 5; i++) mbar_init(sb + B_KR + 8 * i, 1);
      }
      asm volatile("fence.mbarrier_init.release.cluster;" ::: "memory");
    }
    __syncwarp();
    bar_arrive(0, 384);
    if (threadIdx.x == 256) {
      if (b < NA) {
        a_issue_stage(P, sb, 0, b >> 4, b & 15); a_issue_stage(P, sb, 1, b >> 4, b & 15);
      } else {
        b_entry(P, sb, b - NA);
      }
    }
    __syncwarp();
  }
  if (b < 128 && threadIdx.x < 64) {
    const int l = threadIdx.x & 31;
    if (threadIdx.x < 32) {
      asm volatile("prefetch.global.L2 [%0];" ::"l"((const uint8_t*)P.xp + (size_t)(b * 16 + (l >> 1)) * 1280 + (l & 1) * 128));
    } else {
      if (l < 20) asm volatile("prefetch.global.L2 [%0];" ::"l"((const uint8_t*)(l < 10 ? P.brep : P.bimp) + (size_t)(b * 5 + (l % 10 >> 1)) * 1280 + (l & 1) * 128));
    }
  }
  if (threadIdx.x == 96) {
    if (b < NA) { prefetch_tmap(&P.x); prefetch_tmap(&P.bre); prefetch_tmap(&P.bim); }
    else { prefetch_tmap(&P.k16); prefetch_tmap(&P.v16); prefetch_tmap(&P.k); prefetch_tmap(&P.v); }
  }
  __syncwarp();
  if (__shfl_sync(0xffffffffu, threadIdx.x >> 5, 0) >= 8) {
    if (b < NA) {
      roleA_prod(P, sb, b);
    } else {
      roleB_serv(P, sb, b - NA);
    }
  } else {
    if (b < NA) {
      roleA_cons(P, sb, b);
    } else {
      roleB_conv(P, sb, b - NA);
    }
  }
}

typedef CUresult (*EncFn)(CUtensorMap*, CUtensorMapDataType, cuuint32_t, void*, const cuuint64_t*, const cuuint64_t*, const cuuint32_t*,
                          const cuuint32_t*, CUtensorMapInterleave, CUtensorMapSwizzle, CUtensorMapL2promotion, CUtensorMapFloatOOBfill);

static void enc(EncFn fn, CUtensorMap* m, const void* base, int rank, const cuuint64_t* dims, const cuuint64_t* str, const cuuint32_t* box,
                CUtensorMapSwizzle sw, CUtensorMapL2promotion promo) {
  cuuint32_t es[5] = {1, 1, 1, 1, 1};
  fn(m, CU_TENSOR_MAP_DATA_TYPE_BFLOAT16, rank, (void*)base, dims, str, box, es, CU_TENSOR_MAP_INTERLEAVE_NONE, sw, promo,
     CU_TENSOR_MAP_FLOAT_OOB_FILL_NONE);
}

extern "C" void kernel_launch(void* const* d_in, const int* in_sizes, int n_in, void* d_out, int out_size) {
  static EncFn fn = nullptr;
  if (!fn) {
    void* f = nullptr; cudaDriverEntryPointQueryResult qr;
    cudaGetDriverEntryPoint("cuTensorMapEncodeTiled", &f, cudaEnableDefault, &qr);
    fn = (EncFn)f;
    cudaFuncSetAttribute(fused_kernel, cudaFuncAttributeMaxDynamicSharedMemorySize, SMEM_BYTES);
  }
  Params P;
  {
    const cuuint64_t dims[5] = {640, 2, 4, 16, 16}, str[4] = {1280, 32 * 1280, 2 * 1280, 128 * 1280};
    const cuuint32_t box[5] = {64, 2, 4, 16, 1};
    enc(fn, &P.x, d_in[0], 5, dims, str, box, CU_TENSOR_MAP_SWIZZLE_128B, CU_TENSOR_MAP_L2_PROMOTION_NONE);
  }
  {
    const cuuint64_t dims[2] = {640, 640}, str[1] = {1280};
    const cuuint32_t box[2] = {64, 128};
    enc(fn, &P.bre, d_in[3], 2, dims, str, box, CU_TENSOR_MAP_SWIZZLE_128B, CU_TENSOR_MAP_L2_PROMOTION_NONE);
    enc(fn, &P.bim, d_in[4], 2, dims, str, box, CU_TENSOR_MAP_SWIZZLE_128B, CU_TENSOR_MAP_L2_PROMOTION_NONE);
    const cuuint32_t boxh[2] = {64, 64};
    enc(fn, &P.cre, d_in[5], 2, dims, str, boxh, CU_TENSOR_MAP_SWIZZLE_128B, CU_TENSOR_MAP_L2_PROMOTION_NONE);
    enc(fn, &P.cim, d_in[6], 2, dims, str, boxh, CU_TENSOR_MAP_SWIZZLE_128B, CU_TENSOR_MAP_L2_PROMOTION_NONE);
  }
  {
    const cuuint64_t dims[3] = {640, 256, 8}, str[2] = {8 * 1280, 1280};
    const cuuint32_t box[3] = {32, 32, 8}, boxk[3] = {32, 33, 8};
    enc(fn, &P.k, d_in[10], 3, dims, str, boxk, CU_TENSOR_MAP_SWIZZLE_64B, CU_TENSOR_MAP_L2_PROMOTION_NONE);
    enc(fn, &P.v, d_in[11], 3, dims, str, box, CU_TENSOR_MAP_SWIZZLE_64B, CU_TENSOR_MAP_L2_PROMOTION_NONE);
    const cuuint32_t box16[3] = {16, 32, 8}, boxk16[3] = {16, 33, 8};
    enc(fn, &P.k16, d_in[10], 3, dims, str, boxk16, CU_TENSOR_MAP_SWIZZLE_32B, CU_TENSOR_MAP_L2_PROMOTION_NONE);
    enc(fn, &P.v16, d_in[11], 3, dims, str, box16, CU_TENSOR_MAP_SWIZZLE_32B, CU_TENSOR_MAP_L2_PROMOTION_NONE);
  }
  {
    const cuuint64_t dims[2] = {640, 2048}, str[1] = {1280};
    const cuuint32_t box[2] = {8, 256};
    enc(fn, &P.q, d_in[9], 2, dims, str, box, CU_TENSOR_MAP_SWIZZLE_NONE, CU_TENSOR_MAP_L2_PROMOTION_NONE);
    const cuuint32_t box16[2] = {16, 256};
    enc(fn, &P.q16, d_in[9], 2, dims, str, box16, CU_TENSOR_MAP_SWIZZLE_32B, CU_TENSOR_MAP_L2_PROMOTION_NONE);
  }
  {
    const cuuint64_t dims[5] = {1280, 2, 4, 16, 16}, str[4] = {5120, 32 * 5120, 2 * 5120, 128 * 5120};
    const cuuint32_t box[5] = {32, 2, 4, 8, 1}, es[5] = {1, 1, 1, 1, 1};
    fn(&P.oa, CU_TENSOR_MAP_DATA_TYPE_FLOAT32, 5, d_out, dims, str, box, es, CU_TENSOR_MAP_INTERLEAVE_NONE, CU_TENSOR_MAP_SWIZZLE_128B,
       CU_TENSOR_MAP_L2_PROMOTION_NONE, CU_TENSOR_MAP_FLOAT_OOB_FILL_NONE);
  }
  {
    const cuuint64_t dims[2] = {1280, 2048}, str[1] = {5120};
    const cuuint32_t box[2] = {8, 256}, boxh[2] = {8, 128}, box4[2] = {4, 128}, es[2] = {1, 1};
    fn(&P.o4, CU_TENSOR_MAP_DATA_TYPE_FLOAT32, 2, d_out, dims, str, box4, es, CU_TENSOR_MAP_INTERLEAVE_NONE, CU_TENSOR_MAP_SWIZZLE_NONE,
       CU_TENSOR_MAP_L2_PROMOTION_NONE, CU_TENSOR_MAP_FLOAT_OOB_FILL_NONE);
    fn(&P.ob, CU_TENSOR_MAP_DATA_TYPE_FLOAT32, 2, d_out, dims, str, box, es, CU_TENSOR_MAP_INTERLEAVE_NONE, CU_TENSOR_MAP_SWIZZLE_NONE,
       CU_TENSOR_MAP_L2_PROMOTION_NONE, CU_TENSOR_MAP_FLOAT_OOB_FILL_NONE);
    fn(&P.oh, CU_TENSOR_MAP_DATA_TYPE_FLOAT32, 2, d_out, dims, str, boxh, es, CU_TENSOR_MAP_INTERLEAVE_NONE, CU_TENSOR_MAP_SWIZZLE_NONE,
       CU_TENSOR_MAP_L2_PROMOTION_NONE, CU_TENSOR_MAP_FLOAT_OOB_FILL_NONE);
  }
  P.xp = (const __nv_bfloat16*)d_in[0];
  P.lre = (const __nv_bfloat16*)d_in[1];
  P.lim = (const __nv_bfloat16*)d_in[2];
  P.logdt = (const __nv_bfloat16*)d_in[7];
  P.dskip = (const __nv_bfloat16*)d_in[8];
  P.brep = (const __nv_bfloat16*)d_in[3];
  P.bimp = (const __nv_bfloat16*)d_in[4];
  P.kp = (const __nv_bfloat16*)d_in[10];
  P.vp = (const __nv_bfloat16*)d_in[11];
  P.shk = (const __nv_bfloat16*)d_in[12];
  P.ssmk = (const __nv_bfloat16*)d_in[13];
  P.ssmd = (const __nv_bfloat16*)d_in[14];
  P.out = (float*)d_out;
  P.zero = 0;
  fused_kernel<<<NA + NB, 384, SMEM_BYTES>>>(P);
}
```
